```python
import torch

def _softmax(x, axis=-1):
    return torch.softmax(x, dim=axis)
def _gelu(x):
    return torch.nn.functional.gelu(x, approximate="tanh")
def _silu(x):
    return torch.nn.functional.silu(x)
def _sigmoid(x):
    return torch.sigmoid(x)
def _layernorm(x, axis=-1, eps=1e-5):
    m = x.mean(dim=axis, keepdim=True)
    v = x.var(dim=axis, keepdim=True, unbiased=False)
    return (x - m) / torch.sqrt(v + eps)
def _scatter_add(tgt, idx, src, axis=0):
    return tgt.clone().index_add_(axis, idx, src)
def _segment_sum(src, seg, n):
    out = torch.zeros((n,) + src.shape[1:], dtype=src.dtype)
    return out.index_add_(0, seg, src)
def _pad(x, pw):
    flat = tuple(v for pair in reversed(pw) for v in pair)
    return torch.nn.functional.pad(x, flat)

kernel_name = 'parallel_sum__gqa_block_cached__mixer_channel_mlp__decode'

def setup_inputs():

    _w = (lambda a: (lambda t: t.to(torch.bfloat16) if t.is_floating_point() else t)(torch.as_tensor(a)))
    def _A_setup():
        B, Sq, D = 1, 1, 640
        Hq, Hkv, Sk, Dh = 32, 32, 16384, 128
        assert Hq % Hkv == 0, (Hq, Hkv)
        return {
            "x": _w((lambda *s: torch.randn(*s, dtype=torch.bfloat16) * 0.05)(B, Sq, D)),
            "k_cache": _w((lambda *s: torch.randn(*s, dtype=torch.bfloat16) * 3.2)(B, Hkv, Sk, Dh)),
            "v_cache": _w((lambda *s: torch.randn(*s, dtype=torch.bfloat16) * 0.4)(B, Hkv, Sk, Dh)),
            "wq": _w((lambda *s: torch.randn(*s, dtype=torch.bfloat16) * 3.2)(D, Hq * Dh) * (D ** -0.5)),
            "wo": _w((lambda *s: torch.randn(*s, dtype=torch.bfloat16) * 0.4)(Hq * Dh, D) * ((Hq * Dh) ** -0.5)),
        }
    _A_in = _A_setup()

    def _B_setup():
        B, S, D, F = 1, 1, 640, 1728
        return {
            "x": _w((lambda *s: torch.randn(*s, dtype=torch.bfloat16) * 0.05)(B, S, D)),
            "w1": _w((lambda *s: torch.randn(*s, dtype=torch.bfloat16) * 3.2)(D, F) * (D ** -0.5)),
            "b1": _w((lambda *s: torch.randn(*s, dtype=torch.bfloat16) * 0.8)(F)),
            "w2": _w((lambda *s: torch.randn(*s, dtype=torch.bfloat16) * 0.1)(F, D) * (F ** -0.5)),
            "b2": _w((lambda *s: torch.randn(*s, dtype=torch.bfloat16) * 0.1)(D)),
        }
    _B_in = _B_setup()

    return {
        "A_x": _A_in["x"],
        "A_k_cache": _A_in["k_cache"],
        "A_v_cache": _A_in["v_cache"],
        "A_wq": _A_in["wq"],
        "A_wo": _A_in["wo"],
        "B_x": _B_in["x"],
        "B_w1": _B_in["w1"],
        "B_b1": _B_in["b1"],
        "B_w2": _B_in["w2"],
        "B_b2": _B_in["b2"],
    }

def reference(A_x, A_k_cache, A_v_cache, A_wq, A_wo, B_x, B_w1, B_b1, B_w2, B_b2):
    def _A_ref(x, k_cache, v_cache, wq, wo):
        B, Sq, D = x.shape
        Hq, Dh = 32, 128
        Hkv = k_cache.shape[1]
        rep = Hq // Hkv
        q = (lambda x, *d: x.permute(*d))((x @ wq).reshape(B, Sq, Hq, Dh), 0, 2, 1, 3)
        k = (lambda x, n, axis: torch.repeat_interleave(x, n, dim=axis))(k_cache, rep, axis=1)
        v = (lambda x, n, axis: torch.repeat_interleave(x, n, dim=axis))(v_cache, rep, axis=1)
        scores = torch.einsum("bhqd,bhkd->bhqk", q, k) * (Dh ** -0.5)
        p = _softmax(scores, axis=-1)
        o = torch.einsum("bhqk,bhkd->bhqd", p, v)
        return (lambda x, *d: x.permute(*d))(o, 0, 2, 1, 3).reshape(B, Sq, Hq * Dh) @ wo

    def _B_ref(x, w1, b1, w2, b2):
        y = _layernorm(x, axis=-1)
        h = _gelu(torch.einsum("bsd,df->bsf", y, w1) + b1)
        return torch.einsum("bsf,fd->bsd", h, w2) + b2

    x = A_x
    xn = _layernorm(x, axis=-1)
    return x + _A_ref(xn, A_k_cache, A_v_cache, A_wq, A_wo) + _B_ref(xn, B_w1, B_b1, B_w2, B_b2)
```

```cpp
#include <cuda_runtime.h>
#include <cuda_bf16.h>
#include <stdint.h>

namespace {

constexpr int D_MODEL = 640;
constexpr int NHEAD   = 32;
constexpr int DH      = 128;
constexpr int SK      = 16384;
constexpr int FF      = 1728;

constexpr int NSPLIT        = 4;
constexpr int KEYS_PER_CTA  = SK / NSPLIT;
constexpr int TILE          = 64;
constexpr int NSTAGE        = 6;
constexpr int NTILES        = KEYS_PER_CTA / TILE;
constexpr int TILE_BYTES    = TILE * DH * 2;
constexpr int NCONS_WARPS   = 8;
constexpr int NCONS         = NCONS_WARPS * 32;
constexpr int NTHREADS      = NCONS + 32;
constexpr int N_ATTN_CTA    = NHEAD * NSPLIT;
constexpr int N_MLP_CTA     = 4;
constexpr int GRID          = N_ATTN_CTA + N_MLP_CTA;

constexpr float LOG2E = 1.4426950408889634f;

__device__ float    g_part_o[NHEAD][NSPLIT][DH];
__device__ float    g_part_m[NHEAD][NSPLIT];
__device__ float    g_part_l[NHEAD][NSPLIT];
__device__ float    g_headout[NHEAD][D_MODEL];
__device__ float    g_mlp_h[FF];
__device__ float    g_mlp_out[D_MODEL];
__device__ unsigned g_cnt_head[NHEAD];
__device__ unsigned g_cnt_mlp;
__device__ unsigned g_cnt_final;

struct __align__(128) SmemLayout {
    uint8_t  kbuf[NSTAGE][TILE_BYTES];
    uint8_t  vbuf[NSTAGE][TILE_BYTES];
    uint64_t full_k[NSTAGE];
    uint64_t full_v[NSTAGE];
    uint64_t empty[NSTAGE];
    float    xn[D_MODEL];
    float    q[DH];
    float    red[16][DH];
    float    ms[16];
    float    ls[16];
    float    of[DH];
    float    red2[3][D_MODEL];
    unsigned flag;
};

__device__ __forceinline__ float bf16r(float x) {
    return __bfloat162float(__float2bfloat16_rn(x));
}
__device__ __forceinline__ float bf_lo(uint32_t u) { return __uint_as_float(u << 16); }
__device__ __forceinline__ float bf_hi(uint32_t u) { return __uint_as_float(u & 0xffff0000u); }

__device__ __forceinline__ uint32_t smem_u32(const void* p) {
    return (uint32_t)__cvta_generic_to_shared(p);
}
__device__ __forceinline__ void mbar_init(uint64_t* bar, uint32_t count) {
    asm volatile("mbarrier.init.shared::cta.b64 [%0], %1;" ::"r"(smem_u32(bar)), "r"(count) : "memory");
}
__device__ __forceinline__ void mbar_expect_tx(uint64_t* bar, uint32_t bytes) {
    asm volatile("mbarrier.arrive.expect_tx.shared::cta.b64 _, [%0], %1;" ::"r"(smem_u32(bar)), "r"(bytes) : "memory");
}
__device__ __forceinline__ void mbar_arrive(uint64_t* bar) {
    asm volatile("mbarrier.arrive.shared::cta.b64 _, [%0];" ::"r"(smem_u32(bar)) : "memory");
}
__device__ __forceinline__ bool mbar_try_wait(uint64_t* bar, uint32_t parity) {
    uint32_t ok;
    asm volatile(
        "{\n\t.reg .pred p;\n\t"
        "mbarrier.try_wait.parity.shared::cta.b64 p, [%1], %2;\n\t"
        "selp.u32 %0, 1, 0, p;\n\t}"
        : "=r"(ok)
        : "r"(smem_u32(bar)), "r"(parity)
        : "memory");
    return ok != 0;
}
__device__ __forceinline__ void mbar_wait(uint64_t* bar, uint32_t parity) {
    while (!mbar_try_wait(bar, parity)) {
    }
}
__device__ __forceinline__ void bulk_g2s(void* dst, const void* src, uint32_t bytes, uint64_t* bar, uint64_t policy) {
    asm volatile(
        "cp.async.bulk.shared::cluster.global.mbarrier::complete_tx::bytes.L2::cache_hint [%0], [%1], %2, [%3], %4;"
        ::"r"(smem_u32(dst)), "l"(src), "r"(bytes), "r"(smem_u32(bar)), "l"(policy)
        : "memory");
}
__device__ __forceinline__ void bulk_prefetch_l2(const void* src, uint32_t bytes) {
    asm volatile("cp.async.bulk.prefetch.L2.global [%0], %1;" ::"l"(src), "r"(bytes) : "memory");
}
__device__ __forceinline__ uint4 ldg_nc(const void* p) {
    uint4 r;
    asm volatile("ld.global.nc.L1::no_allocate.v4.u32 {%0,%1,%2,%3}, [%4];"
                 : "=r"(r.x), "=r"(r.y), "=r"(r.z), "=r"(r.w)
                 : "l"(p));
    return r;
}
__device__ __forceinline__ uint4 lds128(const void* p) {
    uint4 r;
    asm volatile("ld.shared.v4.u32 {%0,%1,%2,%3}, [%4];"
                 : "=r"(r.x), "=r"(r.y), "=r"(r.z), "=r"(r.w)
                 : "r"(smem_u32(p)));
    return r;
}
__device__ __forceinline__ void named_bar_sync(int id, int n) {
    asm volatile("bar.sync %0, %1;" ::"r"(id), "r"(n) : "memory");
}

__device__ void layernorm_bf16(const float* in, float* out, float* scr, int tid, int nthr, int bar_id) {
    const int lane = tid & 31, wid = tid >> 5, nw = nthr >> 5;
    float s = 0.f;
    for (int i = tid; i < D_MODEL; i += nthr) s += in[i];
#pragma unroll
    for (int o = 16; o > 0; o >>= 1) s += __shfl_xor_sync(0xffffffffu, s, o);
    if (lane == 0) scr[wid] = s;
    named_bar_sync(bar_id, nthr);
    float tot = 0.f;
    for (int w = 0; w < nw; w++) tot += scr[w];
    const float mean = tot * (1.0f / D_MODEL);
    float vs = 0.f;
    for (int i = tid; i < D_MODEL; i += nthr) {
        float d = in[i] - mean;
        vs += d * d;
    }
#pragma unroll
    for (int o = 16; o > 0; o >>= 1) vs += __shfl_xor_sync(0xffffffffu, vs, o);
    if (lane == 0) scr[32 + wid] = vs;
    named_bar_sync(bar_id, nthr);
    float vtot = 0.f;
    for (int w = 0; w < nw; w++) vtot += scr[32 + w];
    const float m_b   = bf16r(mean);
    const float v_b   = bf16r(vtot * (1.0f / D_MODEL));
    const float den   = bf16r(sqrtf(bf16r(v_b + 1e-5f)));
    for (int i = tid; i < D_MODEL; i += nthr) {
        float d = bf16r(in[i] - m_b);
        out[i]  = bf16r(d / den);
    }
    named_bar_sync(bar_id, nthr);
}

__device__ __forceinline__ float gelu_tanh(float x) {
    const float k0 = 0.7978845608028654f, k1 = 0.044715f;
    float inner = k0 * (x + k1 * x * x * x);
    return 0.5f * x * (1.0f + tanhf(inner));
}

__device__ void final_output(const __nv_bfloat16* __restrict__ x, __nv_bfloat16* __restrict__ out, int tid, int nthr) {
    __threadfence();
    for (int n = tid; n < D_MODEL; n += nthr) {
        float acc = 0.f;
#pragma unroll 8
        for (int h = 0; h < NHEAD; h++) acc += __ldcg(&g_headout[h][n]);
        float a = bf16r(acc);
        float t = bf16r(__bfloat162float(x[n]) + a);
        float z = __ldcg(&g_mlp_out[n]);
        out[n]  = __float2bfloat16_rn(t + z);
    }
    if (tid == 0) {
        g_cnt_final = 0;
        g_cnt_mlp   = 0;
    }
    if (tid < NHEAD) g_cnt_head[tid] = 0;
}

__global__ void __launch_bounds__(NTHREADS, 1)
fused_decode_kernel(const __nv_bfloat16* __restrict__ x,
                    const __nv_bfloat16* __restrict__ kc,
                    const __nv_bfloat16* __restrict__ vc,
                    const __nv_bfloat16* __restrict__ wq,
                    const __nv_bfloat16* __restrict__ wo,
                    const __nv_bfloat16* __restrict__ w1,
                    const __nv_bfloat16* __restrict__ b1,
                    const __nv_bfloat16* __restrict__ w2,
                    const __nv_bfloat16* __restrict__ b2,
                    __nv_bfloat16* __restrict__ out) {
    extern __shared__ uint8_t smem_raw[];
    SmemLayout& sm = *reinterpret_cast<SmemLayout*>(smem_raw);
    const int tid  = threadIdx.x;
    const int lane = tid & 31;
    const int wid  = tid >> 5;
    const int cta  = blockIdx.x;

    if (cta < N_ATTN_CTA) {
        const int h     = cta / NSPLIT;
        const int split = cta % NSPLIT;
        const uint8_t* kbase = reinterpret_cast<const uint8_t*>(kc) + ((size_t)h * SK + (size_t)split * KEYS_PER_CTA) * (DH * 2);
        const uint8_t* vbase = reinterpret_cast<const uint8_t*>(vc) + ((size_t)h * SK + (size_t)split * KEYS_PER_CTA) * (DH * 2);

        if (tid == 0) {
            for (int s = 0; s < NSTAGE; s++) {
                mbar_init(&sm.full_k[s], 1);
                mbar_init(&sm.full_v[s], 1);
                mbar_init(&sm.empty[s], NCONS_WARPS);
            }
            asm volatile("fence.mbarrier_init.release.cluster;" ::: "memory");
        }
        __syncthreads();

        if (wid == NCONS_WARPS) {
            if (lane == 0) {
                uint64_t policy;
                asm volatile("createpolicy.fractional.L2::evict_first.b64 %0, 1.0;" : "=l"(policy));
                for (int t = 0; t < NTILES; t++) {
                    const int s = t % NSTAGE;
                    if (t >= NSTAGE) mbar_wait(&sm.empty[s], ((t / NSTAGE) - 1) & 1);
                    mbar_expect_tx(&sm.full_k[s], TILE_BYTES);
                    bulk_g2s(sm.kbuf[s], kbase + (size_t)t * TILE_BYTES, TILE_BYTES, &sm.full_k[s], policy);
                    mbar_expect_tx(&sm.full_v[s], TILE_BYTES);
                    bulk_g2s(sm.vbuf[s], vbase + (size_t)t * TILE_BYTES, TILE_BYTES, &sm.full_v[s], policy);
                    if (t == NTILES - 12) {
                        bulk_prefetch_l2(reinterpret_cast<const uint8_t*>(wo) + ((size_t)h * DH + split * 32) * (D_MODEL * 2),
                                         32 * D_MODEL * 2);
                    }
                }
            }
            return;
        }

        for (int i = tid; i < D_MODEL; i += NCONS) sm.xn[i] = __bfloat162float(x[i]);
        named_bar_sync(1, NCONS);
        layernorm_bf16(sm.xn, sm.xn, &sm.red[0][0], tid, NCONS, 1);

        {
            const int l16 = tid & 15;
            const int rg  = tid >> 4;
            float acc[8];
#pragma unroll
            for (int j = 0; j < 8; j++) acc[j] = 0.f;
            const uint8_t* wbase = reinterpret_cast<const uint8_t*>(wq) + (size_t)h * DH * 2 + l16 * 16;
#pragma unroll 1
            for (int it = 0; it < 4; it++) {
                uint4 w[10];
#pragma unroll
                for (int u = 0; u < 10; u++) {
                    const int row = rg + 16 * (it * 10 + u);
                    w[u] = ldg_nc(wbase + (size_t)row * (NHEAD * DH * 2));
                }
#pragma unroll
                for (int u = 0; u < 10; u++) {
                    const float xv = sm.xn[rg + 16 * (it * 10 + u)];
                    acc[0] += xv * bf_lo(w[u].x); acc[1] += xv * bf_hi(w[u].x);
                    acc[2] += xv * bf_lo(w[u].y); acc[3] += xv * bf_hi(w[u].y);
                    acc[4] += xv * bf_lo(w[u].z); acc[5] += xv * bf_hi(w[u].z);
                    acc[6] += xv * bf_lo(w[u].w); acc[7] += xv * bf_hi(w[u].w);
                }
            }
#pragma unroll
            for (int j = 0; j < 8; j++) sm.red[rg][l16 * 8 + j] = acc[j];
            named_bar_sync(1, NCONS);
            if (tid < DH) {
                float s = 0.f;
#pragma unroll
                for (int r = 0; r < 16; r++) s += sm.red[r][tid];
                sm.q[tid] = bf16r(s);
            }
            named_bar_sync(1, NCONS);
        }

        const int half = lane >> 4;
        const int l16  = lane & 15;
        float qf[8];
#pragma unroll
        for (int j = 0; j < 8; j++) qf[j] = sm.q[l16 * 8 + j];

        float m = -INFINITY, l = 0.f;
        float o[8];
#pragma unroll
        for (int j = 0; j < 8; j++) o[j] = 0.f;
        const float scale = 0.08838834764831845f;
        const int row_off = (wid * 8 + half) * (DH * 2) + l16 * 16;

#pragma unroll 1
        for (int t = 0; t < NTILES; t++) {
            const int s        = t % NSTAGE;
            const uint32_t ph  = (t / NSTAGE) & 1;
            mbar_wait(&sm.full_k[s], ph);
            uint4 kk[4];
#pragma unroll
            for (int i = 0; i < 4; i++) kk[i] = lds128(sm.kbuf[s] + row_off + i * 2 * (DH * 2));
            float sc[4];
#pragma unroll
            for (int i = 0; i < 4; i++) {
                float a = qf[0] * bf_lo(kk[i].x);
                a = fmaf(qf[1], bf_hi(kk[i].x), a);
                a = fmaf(qf[2], bf_lo(kk[i].y), a);
                a = fmaf(qf[3], bf_hi(kk[i].y), a);
                a = fmaf(qf[4], bf_lo(kk[i].z), a);
                a = fmaf(qf[5], bf_hi(kk[i].z), a);
                a = fmaf(qf[6], bf_lo(kk[i].w), a);
                a = fmaf(qf[7], bf_hi(kk[i].w), a);
                sc[i] = a;
            }
#pragma unroll
            for (int off = 8; off > 0; off >>= 1) {
#pragma unroll
                for (int i = 0; i < 4; i++) sc[i] += __shfl_xor_sync(0xffffffffu, sc[i], off);
            }
#pragma unroll
            for (int i = 0; i < 4; i++) sc[i] = bf16r(bf16r(sc[i]) * scale);
            const float mnew = fmaxf(fmaxf(m, fmaxf(sc[0], sc[1])), fmaxf(sc[2], sc[3]));
            const float corr = exp2f((m - mnew) * LOG2E);
            float p[4];
#pragma unroll
            for (int i = 0; i < 4; i++) p[i] = exp2f((sc[i] - mnew) * LOG2E);
            l = l * corr + ((p[0] + p[1]) + (p[2] + p[3]));
            m = mnew;
#pragma unroll
            for (int j = 0; j < 8; j++) o[j] *= corr;

            mbar_wait(&sm.full_v[s], ph);
            uint4 vv[4];
#pragma unroll
            for (int i = 0; i < 4; i++) vv[i] = lds128(sm.vbuf[s] + row_off + i * 2 * (DH * 2));
#pragma unroll
            for (int i = 0; i < 4; i++) {
                o[0] = fmaf(p[i], bf_lo(vv[i].x), o[0]);
                o[1] = fmaf(p[i], bf_hi(vv[i].x), o[1]);
                o[2] = fmaf(p[i], bf_lo(vv[i].y), o[2]);
                o[3] = fmaf(p[i], bf_hi(vv[i].y), o[3]);
                o[4] = fmaf(p[i], bf_lo(vv[i].z), o[4]);
                o[5] = fmaf(p[i], bf_hi(vv[i].z), o[5]);
                o[6] = fmaf(p[i], bf_lo(vv[i].w), o[6]);
                o[7] = fmaf(p[i], bf_hi(vv[i].w), o[7]);
            }
            __syncwarp();
            if (lane == 0) mbar_arrive(&sm.empty[s]);
        }

        {
            const int st = wid * 2 + half;
#pragma unroll
            for (int j = 0; j < 8; j++) sm.red[st][l16 * 8 + j] = o[j];
            if (l16 == 0) {
                sm.ms[st] = m;
                sm.ls[st] = l;
            }
            named_bar_sync(1, NCONS);
            if (tid < DH) {
                float M = sm.ms[0];
#pragma unroll
                for (int i = 1; i < 16; i++) M = fmaxf(M, sm.ms[i]);
                float L = 0.f, O = 0.f;
#pragma unroll
                for (int i = 0; i < 16; i++) {
                    const float w = exp2f((sm.ms[i] - M) * LOG2E);
                    L += w * sm.ls[i];
                    O += w * sm.red[i][tid];
                }
                __stcg(&g_part_o[h][split][tid], O);
                if (tid == 0) {
                    __stcg(&g_part_m[h][split], M);
                    __stcg(&g_part_l[h][split], L);
                }
            }
            __threadfence();
            named_bar_sync(1, NCONS);
            if (tid == 0) sm.flag = atomicAdd(&g_cnt_head[h], 1u);
            named_bar_sync(1, NCONS);
            if (sm.flag != NSPLIT - 1) return;
        }

        __threadfence();
        if (tid < DH) {
            float ms[NSPLIT], M = -INFINITY;
#pragma unroll
            for (int s = 0; s < NSPLIT; s++) {
                ms[s] = __ldcg(&g_part_m[h][s]);
                M = fmaxf(M, ms[s]);
            }
            float L = 0.f, O = 0.f;
#pragma unroll
            for (int s = 0; s < NSPLIT; s++) {
                const float w = exp2f((ms[s] - M) * LOG2E);
                L += w * __ldcg(&g_part_l[h][s]);
                O += w * __ldcg(&g_part_o[h][s][tid]);
            }
            sm.of[tid] = bf16r(O / L);
        }
        named_bar_sync(1, NCONS);
        {
            const int cg = tid % 80;
            const int rgp = tid / 80;
            if (rgp < 3) {
                float acc[8];
#pragma unroll
                for (int j = 0; j < 8; j++) acc[j] = 0.f;
                const uint8_t* wbase = reinterpret_cast<const uint8_t*>(wo) + (size_t)h * DH * (D_MODEL * 2) + cg * 16;
#pragma unroll 1
                for (int r0 = rgp; r0 < DH; r0 += 3 * 11) {
                    uint4 w[11];
#pragma unroll
                    for (int u = 0; u < 11; u++) {
                        const int row = r0 + 3 * u;
                        if (row < DH) w[u] = ldg_nc(wbase + (size_t)row * (D_MODEL * 2));
                    }
#pragma unroll
                    for (int u = 0; u < 11; u++) {
                        const int row = r0 + 3 * u;
                        if (row < DH) {
                            const float xv = sm.of[row];
                            acc[0] += xv * bf_lo(w[u].x); acc[1] += xv * bf_hi(w[u].x);
                            acc[2] += xv * bf_lo(w[u].y); acc[3] += xv * bf_hi(w[u].y);
                            acc[4] += xv * bf_lo(w[u].z); acc[5] += xv * bf_hi(w[u].z);
                            acc[6] += xv * bf_lo(w[u].w); acc[7] += xv * bf_hi(w[u].w);
                        }
                    }
                }
#pragma unroll
                for (int j = 0; j < 8; j++) sm.red2[rgp][cg * 8 + j] = acc[j];
            }
            named_bar_sync(1, NCONS);
            for (int n = tid; n < D_MODEL; n += NCONS)
                __stcg(&g_headout[h][n], sm.red2[0][n] + sm.red2[1][n] + sm.red2[2][n]);
        }
        __threadfence();
        named_bar_sync(1, NCONS);
        if (tid == 0) sm.flag = atomicAdd(&g_cnt_final, 1u);
        named_bar_sync(1, NCONS);
        if (sm.flag == NHEAD) final_output(x, out, tid, NCONS);
        return;
    }

    {
        const int mc = cta - N_ATTN_CTA;
        for (int i = tid; i < D_MODEL; i += NTHREADS) sm.xn[i] = __bfloat162float(x[i]);
        named_bar_sync(1, NTHREADS);
        layernorm_bf16(sm.xn, sm.xn, &sm.red[0][0], tid, NTHREADS, 1);
        layernorm_bf16(sm.xn, sm.xn, &sm.red[0][0], tid, NTHREADS, 1);

        {
            constexpr int CPC = FF / N_MLP_CTA;
            constexpr int NCG = CPC / 8;
            constexpr int NRG = 5;
            const int cg = tid % NCG, rg = tid / NCG;
            float* redm = reinterpret_cast<float*>(sm.kbuf);
            if (rg < NRG) {
                float acc[8];
#pragma unroll
                for (int j = 0; j < 8; j++) acc[j] = 0.f;
                const uint8_t* wbase = reinterpret_cast<const uint8_t*>(w1) + (size_t)(mc * CPC + cg * 8) * 2;
#pragma unroll 1
                for (int it = 0; it < 16; it++) {
                    uint4 w[8];
#pragma unroll
                    for (int u = 0; u < 8; u++) {
                        const int row = rg * 128 + it * 8 + u;
                        w[u] = ldg_nc(wbase + (size_t)row * (FF * 2));
                    }
#pragma unroll
                    for (int u = 0; u < 8; u++) {
                        const float xv = sm.xn[rg * 128 + it * 8 + u];
                        acc[0] += xv * bf_lo(w[u].x); acc[1] += xv * bf_hi(w[u].x);
                        acc[2] += xv * bf_lo(w[u].y); acc[3] += xv * bf_hi(w[u].y);
                        acc[4] += xv * bf_lo(w[u].z); acc[5] += xv * bf_hi(w[u].z);
                        acc[6] += xv * bf_lo(w[u].w); acc[7] += xv * bf_hi(w[u].w);
                    }
                }
#pragma unroll
                for (int j = 0; j < 8; j++) redm[rg * CPC + cg * 8 + j] = acc[j];
            }
            __syncthreads();
            for (int c = tid; c < CPC; c += NTHREADS) {
                float s = 0.f;
#pragma unroll
                for (int r = 0; r < NRG; r++) s += redm[r * CPC + c];
                const int f = mc * CPC + c;
                float u = bf16r(bf16r(s) + __bfloat162float(b1[f]));
                __stcg(&g_mlp_h[f], bf16r(gelu_tanh(u)));
            }
            __threadfence();
            __syncthreads();
            if (tid == 0) sm.flag = atomicAdd(&g_cnt_mlp, 1u);
            __syncthreads();
            if (sm.flag != N_MLP_CTA - 1) return;
        }
        __threadfence();
        {
            float* hs = reinterpret_cast<float*>(sm.vbuf);
            for (int i = tid; i < FF; i += NTHREADS) hs[i] = __ldcg(&g_mlp_h[i]);
            __syncthreads();
            const int cg = tid % 80, rgp = tid / 80;
            if (rgp < 3) {
                float acc[8];
#pragma unroll
                for (int j = 0; j < 8; j++) acc[j] = 0.f;
                const uint8_t* wbase = reinterpret_cast<const uint8_t*>(w2) + cg * 16;
#pragma unroll 1
                for (int it = 0; it < 576 / 12; it++) {
                    uint4 w[12];
#pragma unroll
                    for (int u = 0; u < 12; u++) {
                        const int row = rgp * 576 + it * 12 + u;
                        w[u] = ldg_nc(wbase + (size_t)row * (D_MODEL * 2));
                    }
#pragma unroll
                    for (int u = 0; u < 12; u++) {
                        const float xv = hs[rgp * 576 + it * 12 + u];
                        acc[0] += xv * bf_lo(w[u].x); acc[1] += xv * bf_hi(w[u].x);
                        acc[2] += xv * bf_lo(w[u].y); acc[3] += xv * bf_hi(w[u].y);
                        acc[4] += xv * bf_lo(w[u].z); acc[5] += xv * bf_hi(w[u].z);
                        acc[6] += xv * bf_lo(w[u].w); acc[7] += xv * bf_hi(w[u].w);
                    }
                }
#pragma unroll
                for (int j = 0; j < 8; j++) sm.red2[rgp][cg * 8 + j] = acc[j];
            }
            __syncthreads();
            for (int n = tid; n < D_MODEL; n += NTHREADS) {
                float s = sm.red2[0][n] + sm.red2[1][n] + sm.red2[2][n];
                __stcg(&g_mlp_out[n], bf16r(bf16r(s) + __bfloat162float(b2[n])));
            }
            __threadfence();
            __syncthreads();
            if (tid == 0) sm.flag = atomicAdd(&g_cnt_final, 1u);
            __syncthreads();
            if (sm.flag == NHEAD) final_output(x, out, tid, NTHREADS);
        }
    }
}

}

extern "C" void kernel_launch(void* const* d_in, const int* in_sizes, int n_in, void* d_out, int out_size) {
    const __nv_bfloat16* x  = (const __nv_bfloat16*)d_in[0];
    const __nv_bfloat16* kc = (const __nv_bfloat16*)d_in[1];
    const __nv_bfloat16* vc = (const __nv_bfloat16*)d_in[2];
    const __nv_bfloat16* wq = (const __nv_bfloat16*)d_in[3];
    const __nv_bfloat16* wo = (const __nv_bfloat16*)d_in[4];
    const __nv_bfloat16* w1 = (const __nv_bfloat16*)d_in[6];
    const __nv_bfloat16* b1 = (const __nv_bfloat16*)d_in[7];
    const __nv_bfloat16* w2 = (const __nv_bfloat16*)d_in[8];
    const __nv_bfloat16* b2 = (const __nv_bfloat16*)d_in[9];
    __nv_bfloat16* out = (__nv_bfloat16*)d_out;

    static bool attr_set = false;
    if (!attr_set) {
        cudaFuncSetAttribute(fused_decode_kernel, cudaFuncAttributeMaxDynamicSharedMemorySize, (int)sizeof(SmemLayout));
        attr_set = true;
    }
    fused_decode_kernel<<<GRID, NTHREADS, sizeof(SmemLayout)>>>(x, kc, vc, wq, wo, w1, b1, w2, b2, out);
}
```

```cpp
#include <cuda_runtime.h>
#include <cuda_bf16.h>
#include <stdint.h>

namespace {

constexpr int D_MODEL = 640;
constexpr int NHEAD   = 32;
constexpr int DH      = 128;
constexpr int SK      = 16384;
constexpr int FF      = 1728;

constexpr int NSPLIT        = 4;
constexpr int KEYS_PER_CTA  = SK / NSPLIT;
constexpr int TILE          = 64;
constexpr int NSTAGE        = 6;
constexpr int NTILES        = KEYS_PER_CTA / TILE;
constexpr int TILE_BYTES    = TILE * DH * 2;
constexpr int NCONS_WARPS   = 8;
constexpr int NCONS         = NCONS_WARPS * 32;
constexpr int NTHREADS      = NCONS + 32;
constexpr int N_ATTN_CTA    = NHEAD * NSPLIT;
constexpr int N_MLP_CTA     = 4;
constexpr int GRID          = N_ATTN_CTA + N_MLP_CTA;
constexpr int NFINAL        = NHEAD + N_MLP_CTA;

constexpr float LOG2E = 1.4426950408889634f;

__device__ float    g_part_o[NHEAD][NSPLIT][DH];
__device__ float    g_part_m[NHEAD][NSPLIT];
__device__ float    g_part_l[NHEAD][NSPLIT];
__device__ float    g_headout[NHEAD][D_MODEL];
__device__ float    g_mlp_part[N_MLP_CTA][D_MODEL];
__device__ unsigned g_cnt_head[NHEAD];
__device__ unsigned g_cnt_final;

struct __align__(128) SmemLayout {
    uint8_t  kbuf[NSTAGE][TILE_BYTES];
    uint8_t  vbuf[NSTAGE][TILE_BYTES];
    uint64_t full_k[NSTAGE];
    uint64_t full_v[NSTAGE];
    uint64_t empty[NSTAGE];
    float    xn[D_MODEL];
    float    q[DH];
    float    red[16][DH];
    float    ms[16];
    float    ls[16];
    float    of[DH];
    float    red2[3][D_MODEL];
    unsigned flag;
};

__device__ __forceinline__ float bf16r(float x) {
    return __bfloat162float(__float2bfloat16_rn(x));
}
__device__ __forceinline__ float bf_lo(uint32_t u) { return __uint_as_float(u << 16); }
__device__ __forceinline__ float bf_hi(uint32_t u) { return __uint_as_float(u & 0xffff0000u); }

__device__ __forceinline__ uint32_t smem_u32(const void* p) {
    return (uint32_t)__cvta_generic_to_shared(p);
}
__device__ __forceinline__ void mbar_init(uint64_t* bar, uint32_t count) {
    asm volatile("mbarrier.init.shared::cta.b64 [%0], %1;" ::"r"(smem_u32(bar)), "r"(count) : "memory");
}
__device__ __forceinline__ void mbar_expect_tx(uint64_t* bar, uint32_t bytes) {
    asm volatile("mbarrier.arrive.expect_tx.shared::cta.b64 _, [%0], %1;" ::"r"(smem_u32(bar)), "r"(bytes) : "memory");
}
__device__ __forceinline__ void mbar_arrive(uint64_t* bar) {
    asm volatile("mbarrier.arrive.shared::cta.b64 _, [%0];" ::"r"(smem_u32(bar)) : "memory");
}
__device__ __forceinline__ bool mbar_try_wait(uint64_t* bar, uint32_t parity) {
    uint32_t ok;
    asm volatile(
        "{\n\t.reg .pred p;\n\t"
        "mbarrier.try_wait.parity.shared::cta.b64 p, [%1], %2;\n\t"
        "selp.u32 %0, 1, 0, p;\n\t}"
        : "=r"(ok)
        : "r"(smem_u32(bar)), "r"(parity)
        : "memory");
    return ok != 0;
}
__device__ __forceinline__ void mbar_wait(uint64_t* bar, uint32_t parity) {
    while (!mbar_try_wait(bar, parity)) {
    }
}
__device__ __forceinline__ void bulk_g2s(void* dst, const void* src, uint32_t bytes, uint64_t* bar, uint64_t policy) {
    asm volatile(
        "cp.async.bulk.shared::cluster.global.mbarrier::complete_tx::bytes.L2::cache_hint [%0], [%1], %2, [%3], %4;"
        ::"r"(smem_u32(dst)), "l"(src), "r"(bytes), "r"(smem_u32(bar)), "l"(policy)
        : "memory");
}
__device__ __forceinline__ void bulk_prefetch_l2(const void* src, uint32_t bytes) {
    asm volatile("cp.async.bulk.prefetch.L2.global [%0], %1;" ::"l"(src), "r"(bytes) : "memory");
}
__device__ __forceinline__ uint4 ldg_nc(const void* p) {
    uint4 r;
    asm volatile("ld.global.nc.L1::no_allocate.v4.u32 {%0,%1,%2,%3}, [%4];"
                 : "=r"(r.x), "=r"(r.y), "=r"(r.z), "=r"(r.w)
                 : "l"(p));
    return r;
}
__device__ __forceinline__ uint4 lds128(const void* p) {
    uint4 r;
    asm volatile("ld.shared.v4.u32 {%0,%1,%2,%3}, [%4];"
                 : "=r"(r.x), "=r"(r.y), "=r"(r.z), "=r"(r.w)
                 : "r"(smem_u32(p)));
    return r;
}
__device__ __forceinline__ void named_bar_sync(int id, int n) {
    asm volatile("bar.sync %0, %1;" ::"r"(id), "r"(n) : "memory");
}

__device__ void layernorm_bf16(const float* in, float* out, float* scr, int tid, int nthr, int bar_id) {
    const int lane = tid & 31, wid = tid >> 5, nw = nthr >> 5;
    float s = 0.f;
    for (int i = tid; i < D_MODEL; i += nthr) s += in[i];
#pragma unroll
    for (int o = 16; o > 0; o >>= 1) s += __shfl_xor_sync(0xffffffffu, s, o);
    if (lane == 0) scr[wid] = s;
    named_bar_sync(bar_id, nthr);
    float tot = 0.f;
    for (int w = 0; w < nw; w++) tot += scr[w];
    const float mean = tot * (1.0f / D_MODEL);
    float vs = 0.f;
    for (int i = tid; i < D_MODEL; i += nthr) {
        float d = in[i] - mean;
        vs += d * d;
    }
#pragma unroll
    for (int o = 16; o > 0; o >>= 1) vs += __shfl_xor_sync(0xffffffffu, vs, o);
    if (lane == 0) scr[32 + wid] = vs;
    named_bar_sync(bar_id, nthr);
    float vtot = 0.f;
    for (int w = 0; w < nw; w++) vtot += scr[32 + w];
    const float m_b   = bf16r(mean);
    const float v_b   = bf16r(vtot * (1.0f / D_MODEL));
    const float den   = bf16r(sqrtf(bf16r(v_b + 1e-5f)));
    for (int i = tid; i < D_MODEL; i += nthr) {
        float d = bf16r(in[i] - m_b);
        out[i]  = bf16r(d / den);
    }
    named_bar_sync(bar_id, nthr);
}

__device__ __forceinline__ float gelu_tanh(float x) {
    const float k0 = 0.7978845608028654f, k1 = 0.044715f;
    float inner = k0 * (x + k1 * x * x * x);
    return 0.5f * x * (1.0f + tanhf(inner));
}

__device__ void final_output(const __nv_bfloat16* __restrict__ x, const __nv_bfloat16* __restrict__ b2,
                             __nv_bfloat16* __restrict__ out, int tid, int nthr) {
    __threadfence();
    for (int n = tid; n < D_MODEL; n += nthr) {
        float acc = 0.f;
#pragma unroll 8
        for (int h = 0; h < NHEAD; h++) acc += __ldcg(&g_headout[h][n]);
        float a = bf16r(acc);
        float t = bf16r(__bfloat162float(x[n]) + a);
        float zs = 0.f;
#pragma unroll
        for (int c = 0; c < N_MLP_CTA; c++) zs += __ldcg(&g_mlp_part[c][n]);
        float z = bf16r(bf16r(zs) + __bfloat162float(b2[n]));
        out[n]  = __float2bfloat16_rn(t + z);
    }
    if (tid == 0) g_cnt_final = 0;
    if (tid < NHEAD) g_cnt_head[tid] = 0;
}

__global__ void __launch_bounds__(NTHREADS, 1)
fused_decode_kernel(const __nv_bfloat16* __restrict__ x,
                    const __nv_bfloat16* __restrict__ kc,
                    const __nv_bfloat16* __restrict__ vc,
                    const __nv_bfloat16* __restrict__ wq,
                    const __nv_bfloat16* __restrict__ wo,
                    const __nv_bfloat16* __restrict__ w1,
                    const __nv_bfloat16* __restrict__ b1,
                    const __nv_bfloat16* __restrict__ w2,
                    const __nv_bfloat16* __restrict__ b2,
                    __nv_bfloat16* __restrict__ out) {
    extern __shared__ uint8_t smem_raw[];
    SmemLayout& sm = *reinterpret_cast<SmemLayout*>(smem_raw);
    const int tid  = threadIdx.x;
    const int lane = tid & 31;
    const int wid  = tid >> 5;
    const int cta  = blockIdx.x;

    if (cta < N_ATTN_CTA) {
        const int h     = cta / NSPLIT;
        const int split = cta % NSPLIT;
        const uint8_t* kbase = reinterpret_cast<const uint8_t*>(kc) + ((size_t)h * SK + (size_t)split * KEYS_PER_CTA) * (DH * 2);
        const uint8_t* vbase = reinterpret_cast<const uint8_t*>(vc) + ((size_t)h * SK + (size_t)split * KEYS_PER_CTA) * (DH * 2);

        if (tid == 0) {
            for (int s = 0; s < NSTAGE; s++) {
                mbar_init(&sm.full_k[s], 1);
                mbar_init(&sm.full_v[s], 1);
                mbar_init(&sm.empty[s], NCONS_WARPS);
            }
            asm volatile("fence.mbarrier_init.release.cluster;" ::: "memory");
        }
        __syncthreads();

        if (wid == NCONS_WARPS) {
            if (lane == 0) {
                uint64_t policy;
                asm volatile("createpolicy.fractional.L2::evict_first.b64 %0, 1.0;" : "=l"(policy));
                for (int t = 0; t < NTILES; t++) {
                    const int s = t % NSTAGE;
                    if (t >= NSTAGE) mbar_wait(&sm.empty[s], ((t / NSTAGE) - 1) & 1);
                    mbar_expect_tx(&sm.full_k[s], TILE_BYTES);
                    bulk_g2s(sm.kbuf[s], kbase + (size_t)t * TILE_BYTES, TILE_BYTES, &sm.full_k[s], policy);
                    mbar_expect_tx(&sm.full_v[s], TILE_BYTES);
                    bulk_g2s(sm.vbuf[s], vbase + (size_t)t * TILE_BYTES, TILE_BYTES, &sm.full_v[s], policy);
                    if (t == NTILES - 12) {
                        bulk_prefetch_l2(reinterpret_cast<const uint8_t*>(wo) + ((size_t)h * DH + split * 32) * (D_MODEL * 2),
                                         32 * D_MODEL * 2);
                    }
                }
            }
            return;
        }

        for (int i = tid; i < D_MODEL; i += NCONS) sm.xn[i] = __bfloat162float(x[i]);
        named_bar_sync(1, NCONS);
        layernorm_bf16(sm.xn, sm.xn, &sm.red[0][0], tid, NCONS, 1);

        {
            const int l16 = tid & 15;
            const int rg  = tid >> 4;
            float acc[8];
#pragma unroll
            for (int j = 0; j < 8; j++) acc[j] = 0.f;
            const uint8_t* wbase = reinterpret_cast<const uint8_t*>(wq) + (size_t)h * DH * 2 + l16 * 16;
#pragma unroll 1
            for (int it = 0; it < 4; it++) {
                uint4 w[10];
#pragma unroll
                for (int u = 0; u < 10; u++) {
                    const int row = rg + 16 * (it * 10 + u);
                    w[u] = ldg_nc(wbase + (size_t)row * (NHEAD * DH * 2));
                }
#pragma unroll
                for (int u = 0; u < 10; u++) {
                    const float xv = sm.xn[rg + 16 * (it * 10 + u)];
                    acc[0] += xv * bf_lo(w[u].x); acc[1] += xv * bf_hi(w[u].x);
                    acc[2] += xv * bf_lo(w[u].y); acc[3] += xv * bf_hi(w[u].y);
                    acc[4] += xv * bf_lo(w[u].z); acc[5] += xv * bf_hi(w[u].z);
                    acc[6] += xv * bf_lo(w[u].w); acc[7] += xv * bf_hi(w[u].w);
                }
            }
#pragma unroll
            for (int j = 0; j < 8; j++) sm.red[rg][l16 * 8 + j] = acc[j];
            named_bar_sync(1, NCONS);
            if (tid < DH) {
                float s = 0.f;
#pragma unroll
                for (int r = 0; r < 16; r++) s += sm.red[r][tid];
                sm.q[tid] = bf16r(s);
            }
            named_bar_sync(1, NCONS);
        }

        const int half = lane >> 4;
        const int l16  = lane & 15;
        float qf[8];
#pragma unroll
        for (int j = 0; j < 8; j++) qf[j] = sm.q[l16 * 8 + j];

        float m = -INFINITY, l = 0.f;
        float o[8];
#pragma unroll
        for (int j = 0; j < 8; j++) o[j] = 0.f;
        const float scale = 0.08838834764831845f;
        const int row_off = (wid * 8 + half) * (DH * 2) + l16 * 16;

#pragma unroll 1
        for (int t = 0; t < NTILES; t++) {
            const int s        = t % NSTAGE;
            const uint32_t ph  = (t / NSTAGE) & 1;
            mbar_wait(&sm.full_k[s], ph);
            uint4 kk[4];
#pragma unroll
            for (int i = 0; i < 4; i++) kk[i] = lds128(sm.kbuf[s] + row_off + i * 2 * (DH * 2));
            float sc[4];
#pragma unroll
            for (int i = 0; i < 4; i++) {
                float a = qf[0] * bf_lo(kk[i].x);
                a = fmaf(qf[1], bf_hi(kk[i].x), a);
                a = fmaf(qf[2], bf_lo(kk[i].y), a);
                a = fmaf(qf[3], bf_hi(kk[i].y), a);
                a = fmaf(qf[4], bf_lo(kk[i].z), a);
                a = fmaf(qf[5], bf_hi(kk[i].z), a);
                a = fmaf(qf[6], bf_lo(kk[i].w), a);
                a = fmaf(qf[7], bf_hi(kk[i].w), a);
                sc[i] = a;
            }
#pragma unroll
            for (int off = 8; off > 0; off >>= 1) {
#pragma unroll
                for (int i = 0; i < 4; i++) sc[i] += __shfl_xor_sync(0xffffffffu, sc[i], off);
            }
#pragma unroll
            for (int i = 0; i < 4; i++) sc[i] = bf16r(bf16r(sc[i]) * scale);
            const float mnew = fmaxf(fmaxf(m, fmaxf(sc[0], sc[1])), fmaxf(sc[2], sc[3]));
            const float corr = exp2f((m - mnew) * LOG2E);
            float p[4];
#pragma unroll
            for (int i = 0; i < 4; i++) p[i] = exp2f((sc[i] - mnew) * LOG2E);
            l = l * corr + ((p[0] + p[1]) + (p[2] + p[3]));
            m = mnew;
#pragma unroll
            for (int j = 0; j < 8; j++) o[j] *= corr;

            mbar_wait(&sm.full_v[s], ph);
            uint4 vv[4];
#pragma unroll
            for (int i = 0; i < 4; i++) vv[i] = lds128(sm.vbuf[s] + row_off + i * 2 * (DH * 2));
#pragma unroll
            for (int i = 0; i < 4; i++) {
                o[0] = fmaf(p[i], bf_lo(vv[i].x), o[0]);
                o[1] = fmaf(p[i], bf_hi(vv[i].x), o[1]);
                o[2] = fmaf(p[i], bf_lo(vv[i].y), o[2]);
                o[3] = fmaf(p[i], bf_hi(vv[i].y), o[3]);
                o[4] = fmaf(p[i], bf_lo(vv[i].z), o[4]);
                o[5] = fmaf(p[i], bf_hi(vv[i].z), o[5]);
                o[6] = fmaf(p[i], bf_lo(vv[i].w), o[6]);
                o[7] = fmaf(p[i], bf_hi(vv[i].w), o[7]);
            }
            __syncwarp();
            if (lane == 0) mbar_arrive(&sm.empty[s]);
        }

        {
            const int st = wid * 2 + half;
#pragma unroll
            for (int j = 0; j < 8; j++) sm.red[st][l16 * 8 + j] = o[j];
            if (l16 == 0) {
                sm.ms[st] = m;
                sm.ls[st] = l;
            }
            named_bar_sync(1, NCONS);
            if (tid < DH) {
                float M = sm.ms[0];
#pragma unroll
                for (int i = 1; i < 16; i++) M = fmaxf(M, sm.ms[i]);
                float L = 0.f, O = 0.f;
#pragma unroll
                for (int i = 0; i < 16; i++) {
                    const float w = exp2f((sm.ms[i] - M) * LOG2E);
                    L += w * sm.ls[i];
                    O += w * sm.red[i][tid];
                }
                __stcg(&g_part_o[h][split][tid], O);
                if (tid == 0) {
                    __stcg(&g_part_m[h][split], M);
                    __stcg(&g_part_l[h][split], L);
                }
            }
            __threadfence();
            named_bar_sync(1, NCONS);
            if (tid == 0) sm.flag = atomicAdd(&g_cnt_head[h], 1u);
            named_bar_sync(1, NCONS);
            if (sm.flag != NSPLIT - 1) return;
        }

        __threadfence();
        if (tid < DH) {
            float ms[NSPLIT], M = -INFINITY;
#pragma unroll
            for (int s = 0; s < NSPLIT; s++) {
                ms[s] = __ldcg(&g_part_m[h][s]);
                M = fmaxf(M, ms[s]);
            }
            float L = 0.f, O = 0.f;
#pragma unroll
            for (int s = 0; s < NSPLIT; s++) {
                const float w = exp2f((ms[s] - M) * LOG2E);
                L += w * __ldcg(&g_part_l[h][s]);
                O += w * __ldcg(&g_part_o[h][s][tid]);
            }
            sm.of[tid] = bf16r(O / L);
        }
        named_bar_sync(1, NCONS);
        {
            const int cg = tid % 80;
            const int rgp = tid / 80;
            if (rgp < 3) {
                float acc[8];
#pragma unroll
                for (int j = 0; j < 8; j++) acc[j] = 0.f;
                const uint8_t* wbase = reinterpret_cast<const uint8_t*>(wo) + (size_t)h * DH * (D_MODEL * 2) + cg * 16;
#pragma unroll 1
                for (int r0 = rgp; r0 < DH; r0 += 3 * 11) {
                    uint4 w[11];
#pragma unroll
                    for (int u = 0; u < 11; u++) {
                        const int row = r0 + 3 * u;
                        if (row < DH) w[u] = ldg_nc(wbase + (size_t)row * (D_MODEL * 2));
                    }
#pragma unroll
                    for (int u = 0; u < 11; u++) {
                        const int row = r0 + 3 * u;
                        if (row < DH) {
                            const float xv = sm.of[row];
                            acc[0] += xv * bf_lo(w[u].x); acc[1] += xv * bf_hi(w[u].x);
                            acc[2] += xv * bf_lo(w[u].y); acc[3] += xv * bf_hi(w[u].y);
                            acc[4] += xv * bf_lo(w[u].z); acc[5] += xv * bf_hi(w[u].z);
                            acc[6] += xv * bf_lo(w[u].w); acc[7] += xv * bf_hi(w[u].w);
                        }
                    }
                }
#pragma unroll
                for (int j = 0; j < 8; j++) sm.red2[rgp][cg * 8 + j] = acc[j];
            }
            named_bar_sync(1, NCONS);
            for (int n = tid; n < D_MODEL; n += NCONS)
                __stcg(&g_headout[h][n], sm.red2[0][n] + sm.red2[1][n] + sm.red2[2][n]);
        }
        __threadfence();
        named_bar_sync(1, NCONS);
        if (tid == 0) sm.flag = atomicAdd(&g_cnt_final, 1u);
        named_bar_sync(1, NCONS);
        if (sm.flag == NFINAL - 1) final_output(x, b2, out, tid, NCONS);
        return;
    }

    {
        const int mc = cta - N_ATTN_CTA;
        for (int i = tid; i < D_MODEL; i += NTHREADS) sm.xn[i] = __bfloat162float(x[i]);
        named_bar_sync(1, NTHREADS);
        layernorm_bf16(sm.xn, sm.xn, &sm.red[0][0], tid, NTHREADS, 1);
        layernorm_bf16(sm.xn, sm.xn, &sm.red[0][0], tid, NTHREADS, 1);

        constexpr int CPC = FF / N_MLP_CTA;
        float* hs = reinterpret_cast<float*>(sm.vbuf);
        {
            constexpr int NCG = CPC / 8;
            constexpr int NRG = 5;
            const int cg = tid % NCG, rg = tid / NCG;
            float* redm = reinterpret_cast<float*>(sm.kbuf);
            if (rg < NRG) {
                float acc[8];
#pragma unroll
                for (int j = 0; j < 8; j++) acc[j] = 0.f;
                const uint8_t* wbase = reinterpret_cast<const uint8_t*>(w1) + (size_t)(mc * CPC + cg * 8) * 2;
#pragma unroll 1
                for (int it = 0; it < 8; it++) {
                    uint4 w[16];
#pragma unroll
                    for (int u = 0; u < 16; u++) {
                        const int row = rg * 128 + it * 16 + u;
                        w[u] = ldg_nc(wbase + (size_t)row * (FF * 2));
                    }
#pragma unroll
                    for (int u = 0; u < 16; u++) {
                        const float xv = sm.xn[rg * 128 + it * 16 + u];
                        acc[0] += xv * bf_lo(w[u].x); acc[1] += xv * bf_hi(w[u].x);
                        acc[2] += xv * bf_lo(w[u].y); acc[3] += xv * bf_hi(w[u].y);
                        acc[4] += xv * bf_lo(w[u].z); acc[5] += xv * bf_hi(w[u].z);
                        acc[6] += xv * bf_lo(w[u].w); acc[7] += xv * bf_hi(w[u].w);
                    }
                }
#pragma unroll
                for (int j = 0; j < 8; j++) redm[rg * CPC + cg * 8 + j] = acc[j];
            }
            __syncthreads();
            for (int c = tid; c < CPC; c += NTHREADS) {
                float s = 0.f;
#pragma unroll
                for (int r = 0; r < NRG; r++) s += redm[r * CPC + c];
                const int f = mc * CPC + c;
                float u = bf16r(bf16r(s) + __bfloat162float(b1[f]));
                hs[c] = bf16r(gelu_tanh(u));
            }
            __syncthreads();
        }
        {
            const int cg = tid % 80, rgp = tid / 80;
            if (rgp < 3) {
                float acc[8];
#pragma unroll
                for (int j = 0; j < 8; j++) acc[j] = 0.f;
                const uint8_t* wbase = reinterpret_cast<const uint8_t*>(w2) + (size_t)(mc * CPC) * (D_MODEL * 2) + cg * 16;
#pragma unroll 1
                for (int it = 0; it < 9; it++) {
                    uint4 w[16];
#pragma unroll
                    for (int u = 0; u < 16; u++) {
                        const int row = rgp * 144 + it * 16 + u;
                        w[u] = ldg_nc(wbase + (size_t)row * (D_MODEL * 2));
                    }
#pragma unroll
                    for (int u = 0; u < 16; u++) {
                        const float xv = hs[rgp * 144 + it * 16 + u];
                        acc[0] += xv * bf_lo(w[u].x); acc[1] += xv * bf_hi(w[u].x);
                        acc[2] += xv * bf_lo(w[u].y); acc[3] += xv * bf_hi(w[u].y);
                        acc[4] += xv * bf_lo(w[u].z); acc[5] += xv * bf_hi(w[u].z);
                        acc[6] += xv * bf_lo(w[u].w); acc[7] += xv * bf_hi(w[u].w);
                    }
                }
#pragma unroll
                for (int j = 0; j < 8; j++) sm.red2[rgp][cg * 8 + j] = acc[j];
            }
            __syncthreads();
            for (int n = tid; n < D_MODEL; n += NTHREADS)
                __stcg(&g_mlp_part[mc][n], sm.red2[0][n] + sm.red2[1][n] + sm.red2[2][n]);
            __threadfence();
            __syncthreads();
            if (tid == 0) sm.flag = atomicAdd(&g_cnt_final, 1u);
            __syncthreads();
            if (sm.flag == NFINAL - 1) final_output(x, b2, out, tid, NTHREADS);
        }
    }
}

}

extern "C" void kernel_launch(void* const* d_in, const int* in_sizes, int n_in, void* d_out, int out_size) {
    const __nv_bfloat16* x  = (const __nv_bfloat16*)d_in[0];
    const __nv_bfloat16* kc = (const __nv_bfloat16*)d_in[1];
    const __nv_bfloat16* vc = (const __nv_bfloat16*)d_in[2];
    const __nv_bfloat16* wq = (const __nv_bfloat16*)d_in[3];
    const __nv_bfloat16* wo = (const __nv_bfloat16*)d_in[4];
    const __nv_bfloat16* w1 = (const __nv_bfloat16*)d_in[6];
    const __nv_bfloat16* b1 = (const __nv_bfloat16*)d_in[7];
    const __nv_bfloat16* w2 = (const __nv_bfloat16*)d_in[8];
    const __nv_bfloat16* b2 = (const __nv_bfloat16*)d_in[9];
    __nv_bfloat16* out = (__nv_bfloat16*)d_out;

    static bool attr_set = false;
    if (!attr_set) {
        cudaFuncSetAttribute(fused_decode_kernel, cudaFuncAttributeMaxDynamicSharedMemorySize, (int)sizeof(SmemLayout));
        attr_set = true;
    }
    fused_decode_kernel<<<GRID, NTHREADS, sizeof(SmemLayout)>>>(x, kc, vc, wq, wo, w1, b1, w2, b2, out);
}
```

```cpp
#include <cuda_runtime.h>
#include <cuda_bf16.h>
#include <stdint.h>

namespace {

constexpr int D_MODEL = 640;
constexpr int NHEAD   = 32;
constexpr int DH      = 128;
constexpr int SK      = 16384;
constexpr int FF      = 1728;

#define CFG_TILE 64
#define CFG_NSTAGE 3

constexpr int NSPLIT        = 4;
constexpr int TILE          = CFG_TILE;
constexpr int NSTAGE        = CFG_NSTAGE;
constexpr int NT_HEAD       = SK / TILE;
constexpr int TILE_BYTES    = TILE * DH * 2;
constexpr int NCONS_WARPS   = 8;
constexpr int NCONS         = NCONS_WARPS * 32;
constexpr int NR            = TILE / NCONS_WARPS / 2;
constexpr int NTHREADS      = NCONS + 32;
constexpr int N_ATTN_CTA    = NHEAD * NSPLIT;
constexpr int N_MLP_CTA     = 4;
constexpr int GRID          = N_ATTN_CTA + N_MLP_CTA;
constexpr int OCOLS         = D_MODEL / NSPLIT;
constexpr int SPIN_LIMIT    = 1 << 22;

constexpr float LOG2E = 1.4426950408889634f;

typedef unsigned long long u64;

__device__ __align__(16) u64 g_qpart[NHEAD][NSPLIT][DH];
__device__ __align__(16) u64 g_part[NHEAD][NSPLIT][DH + 2];
__device__ __align__(16) u64 g_headout[NHEAD][D_MODEL];
__device__ __align__(16) u64 g_mlp_part[N_MLP_CTA][D_MODEL];
__device__ unsigned g_ticket[NHEAD];
__device__ unsigned g_epoch;

#define DBG_STAMP(i) do { } while (0)

struct __align__(128) SmemLayout {
    uint8_t  kbuf[NSTAGE][TILE_BYTES];
    uint8_t  vbuf[NSTAGE][TILE_BYTES];
    uint64_t full_k[NSTAGE];
    uint64_t full_v[NSTAGE];
    uint64_t empty[NSTAGE];
    int      valid[NSTAGE];
    float    xn[D_MODEL];
    float    q[DH];
    float    red[16][OCOLS];
    float    ms[16];
    float    ls[16];
    float    of[DH];
    __align__(16) float red2[5][D_MODEL];
};

__device__ __forceinline__ float bf16r(float x) { return __bfloat162float(__float2bfloat16_rn(x)); }
__device__ __forceinline__ float bf_lo(uint32_t u) { return __uint_as_float(u << 16); }
__device__ __forceinline__ float bf_hi(uint32_t u) { return __uint_as_float(u & 0xffff0000u); }

__device__ __forceinline__ uint32_t smem_u32(const void* p) { return (uint32_t)__cvta_generic_to_shared(p); }
__device__ __forceinline__ void mbar_init(uint64_t* bar, uint32_t count) {
    asm volatile("mbarrier.init.shared::cta.b64 [%0], %1;" ::"r"(smem_u32(bar)), "r"(count) : "memory");
}
__device__ __forceinline__ void mbar_expect_tx(uint64_t* bar, uint32_t bytes) {
    asm volatile("mbarrier.arrive.expect_tx.shared::cta.b64 _, [%0], %1;" ::"r"(smem_u32(bar)), "r"(bytes) : "memory");
}
__device__ __forceinline__ void mbar_arrive(uint64_t* bar) {
    asm volatile("mbarrier.arrive.shared::cta.b64 _, [%0];" ::"r"(smem_u32(bar)) : "memory");
}
__device__ __forceinline__ bool mbar_try_wait(uint64_t* bar, uint32_t parity) {
    uint32_t ok;
    asm volatile(
        "{\n\t.reg .pred p;\n\t"
        "mbarrier.try_wait.parity.shared::cta.b64 p, [%1], %2;\n\t"
        "selp.u32 %0, 1, 0, p;\n\t}"
        : "=r"(ok)
        : "r"(smem_u32(bar)), "r"(parity)
        : "memory");
    return ok != 0;
}
__device__ __forceinline__ void mbar_wait(uint64_t* bar, uint32_t parity) {
    while (!mbar_try_wait(bar, parity)) {
    }
}
__device__ __forceinline__ void bulk_g2s(void* dst, const void* src, uint32_t bytes, uint64_t* bar, uint64_t policy) {
    asm volatile(
        "cp.async.bulk.shared::cluster.global.mbarrier::complete_tx::bytes.L2::cache_hint [%0], [%1], %2, [%3], %4;"
        ::"r"(smem_u32(dst)), "l"(src), "r"(bytes), "r"(smem_u32(bar)), "l"(policy)
        : "memory");
}
__device__ __forceinline__ uint4 ldg_nc(const void* p) {
    uint4 r;
    asm volatile("ld.global.nc.L1::no_allocate.v4.u32 {%0,%1,%2,%3}, [%4];"
                 : "=r"(r.x), "=r"(r.y), "=r"(r.z), "=r"(r.w)
                 : "l"(p));
    return r;
}
__device__ __forceinline__ uint4 lds128(const void* p) {
    uint4 r;
    asm volatile("ld.shared.v4.u32 {%0,%1,%2,%3}, [%4];"
                 : "=r"(r.x), "=r"(r.y), "=r"(r.z), "=r"(r.w)
                 : "r"(smem_u32(p)));
    return r;
}
__device__ __forceinline__ void named_bar_sync(int id, int n) {
    asm volatile("bar.sync %0, %1;" ::"r"(id), "r"(n) : "memory");
}
__device__ __forceinline__ void st_ll(u64* p, float v, unsigned tag) {
    const u64 w = ((u64)tag << 32) | (u64)__float_as_uint(v);
    asm volatile("st.relaxed.gpu.global.b64 [%0], %1;" ::"l"(p), "l"(w) : "memory");
}
__device__ __forceinline__ u64 ld_ll(const u64* p) {
    u64 w;
    asm volatile("ld.relaxed.gpu.global.b64 %0, [%1];" : "=l"(w) : "l"(p) : "memory");
    return w;
}
__device__ __forceinline__ void ld_ll2(const u64* p, u64& a, u64& b) {
    asm volatile("ld.relaxed.gpu.global.v2.b64 {%0,%1}, [%2];" : "=l"(a), "=l"(b) : "l"(p) : "memory");
}
__device__ __forceinline__ bool ll_ok(u64 w, unsigned tag) { return (unsigned)(w >> 32) == tag; }
__device__ __forceinline__ float ll_val(u64 w) { return __uint_as_float((unsigned)w); }

__device__ __forceinline__ void fma8(float* acc, float xv, const uint4& w) {
    acc[0] = fmaf(xv, bf_lo(w.x), acc[0]); acc[1] = fmaf(xv, bf_hi(w.x), acc[1]);
    acc[2] = fmaf(xv, bf_lo(w.y), acc[2]); acc[3] = fmaf(xv, bf_hi(w.y), acc[3]);
    acc[4] = fmaf(xv, bf_lo(w.z), acc[4]); acc[5] = fmaf(xv, bf_hi(w.z), acc[5]);
    acc[6] = fmaf(xv, bf_lo(w.w), acc[6]); acc[7] = fmaf(xv, bf_hi(w.w), acc[7]);
}

__device__ void layernorm_bf16(const float* in, float* out, float* scr, int tid, int nthr, int bar_id) {
    const int lane = tid & 31, wid = tid >> 5, nw = nthr >> 5;
    float s = 0.f;
    for (int i = tid; i < D_MODEL; i += nthr) s += in[i];
#pragma unroll
    for (int o = 16; o > 0; o >>= 1) s += __shfl_xor_sync(0xffffffffu, s, o);
    if (lane == 0) scr[wid] = s;
    named_bar_sync(bar_id, nthr);
    float tot = 0.f;
    for (int w = 0; w < nw; w++) tot += scr[w];
    const float mean = tot * (1.0f / D_MODEL);
    float vs = 0.f;
    for (int i = tid; i < D_MODEL; i += nthr) {
        float d = in[i] - mean;
        vs += d * d;
    }
#pragma unroll
    for (int o = 16; o > 0; o >>= 1) vs += __shfl_xor_sync(0xffffffffu, vs, o);
    if (lane == 0) scr[32 + wid] = vs;
    named_bar_sync(bar_id, nthr);
    float vtot = 0.f;
    for (int w = 0; w < nw; w++) vtot += scr[32 + w];
    const float m_b = bf16r(mean);
    const float v_b = bf16r(vtot * (1.0f / D_MODEL));
    const float den = bf16r(sqrtf(bf16r(v_b + 1e-5f)));
    for (int i = tid; i < D_MODEL; i += nthr) {
        float d = bf16r(in[i] - m_b);
        out[i]  = bf16r(d / den);
    }
    named_bar_sync(bar_id, nthr);
}

__device__ __forceinline__ float gelu_tanh(float x) {
    const float k0 = 0.7978845608028654f, k1 = 0.044715f;
    float inner = k0 * (x + k1 * x * x * x);
    return 0.5f * x * (1.0f + tanhf(inner));
}

__global__ void __launch_bounds__(NTHREADS, 1)
fused_decode_kernel(const __nv_bfloat16* __restrict__ x,
                    const __nv_bfloat16* __restrict__ kc,
                    const __nv_bfloat16* __restrict__ vc,
                    const __nv_bfloat16* __restrict__ wq,
                    const __nv_bfloat16* __restrict__ wo,
                    const __nv_bfloat16* __restrict__ w1,
                    const __nv_bfloat16* __restrict__ b1,
                    const __nv_bfloat16* __restrict__ w2,
                    const __nv_bfloat16* __restrict__ b2,
                    __nv_bfloat16* __restrict__ out) {
    extern __shared__ uint8_t smem_raw[];
    SmemLayout& sm = *reinterpret_cast<SmemLayout*>(smem_raw);
    const int tid  = threadIdx.x;
    const int lane = tid & 31;
    const int wid  = tid >> 5;
    const int cta  = blockIdx.x;
    DBG_STAMP(0);

    const unsigned epoch = *reinterpret_cast<volatile unsigned*>(&g_epoch);
    const unsigned tag   = epoch + 1u;

    if (cta < N_ATTN_CTA) {
        const int h     = cta % NHEAD;
        const int split = cta / NHEAD;

        const int l16q = tid & 15;
        const int rgq  = tid >> 4;
        uint4 wqr[10];
        const int cgo = tid % 20;
        const int rgo = tid / 20;
        uint4 wor[11];
        if (wid < NCONS_WARPS) {
            const uint8_t* wbase = reinterpret_cast<const uint8_t*>(wq) + (size_t)h * DH * 2 + l16q * 16;
#pragma unroll
            for (int u = 0; u < 10; u++)
                wqr[u] = ldg_nc(wbase + (size_t)(split * 160 + rgq + 16 * u) * (NHEAD * DH * 2));
        }

        if (tid == 0) {
            for (int s = 0; s < NSTAGE; s++) {
                mbar_init(&sm.full_k[s], 1);
                mbar_init(&sm.full_v[s], 1);
                mbar_init(&sm.empty[s], NCONS_WARPS);
            }
            asm volatile("fence.mbarrier_init.release.cluster;" ::: "memory");
        }
        __syncthreads();

        if (wid == NCONS_WARPS) {
            if (lane == 0) {
                const uint8_t* kbase = reinterpret_cast<const uint8_t*>(kc) + (size_t)h * SK * (DH * 2);
                const uint8_t* vbase = reinterpret_cast<const uint8_t*>(vc) + (size_t)h * SK * (DH * 2);
                uint64_t policy;
                asm volatile("createpolicy.fractional.L2::evict_first.b64 %0, 1.0;" : "=l"(policy));
                const unsigned tbase = epoch * (unsigned)(NT_HEAD + NSPLIT);
                unsigned next = atomicAdd(&g_ticket[h], 1u) - tbase;
                int it = 0;
                for (;; it++) {
                    const int s = it % NSTAGE;
                    const unsigned t = next;
                    if (t < (unsigned)NT_HEAD) next = atomicAdd(&g_ticket[h], 1u) - tbase;
                    if (it >= NSTAGE) mbar_wait(&sm.empty[s], ((it / NSTAGE) - 1) & 1);
                    if (t >= (unsigned)NT_HEAD) {
                        sm.valid[s] = 0;
                        mbar_arrive(&sm.full_k[s]);
                        break;
                    }
                    sm.valid[s] = 1;
                    mbar_expect_tx(&sm.full_k[s], TILE_BYTES);
                    bulk_g2s(sm.kbuf[s], kbase + (size_t)t * TILE_BYTES, TILE_BYTES, &sm.full_k[s], policy);
                    mbar_expect_tx(&sm.full_v[s], TILE_BYTES);
                    bulk_g2s(sm.vbuf[s], vbase + (size_t)t * TILE_BYTES, TILE_BYTES, &sm.full_v[s], policy);
                }
            }
            return;
        }

        if (rgo < 12) {
            const uint8_t* wbase = reinterpret_cast<const uint8_t*>(wo) + (size_t)h * DH * (D_MODEL * 2) + split * (OCOLS * 2) + cgo * 16;
#pragma unroll
            for (int u = 0; u < 11; u++) {
                const int row = rgo + 12 * u;
                if (u < 10 || row < DH) wor[u] = ldg_nc(wbase + (size_t)row * (D_MODEL * 2));
            }
        }

        for (int i = tid; i < D_MODEL; i += NCONS) sm.xn[i] = __bfloat162float(x[i]);
        named_bar_sync(1, NCONS);
        layernorm_bf16(sm.xn, sm.xn, &sm.red[0][0], tid, NCONS, 1);
        DBG_STAMP(4);

        {
            float acc[8];
#pragma unroll
            for (int j = 0; j < 8; j++) acc[j] = 0.f;
#pragma unroll
            for (int u = 0; u < 10; u++) fma8(acc, sm.xn[split * 160 + rgq + 16 * u], wqr[u]);
#pragma unroll
            for (int j = 0; j < 8; j++) sm.red[rgq][l16q * 8 + j] = acc[j];
            DBG_STAMP(5);
            named_bar_sync(1, NCONS);
            if (tid < DH) {
                float s = 0.f;
#pragma unroll
                for (int r = 0; r < 16; r++) s += sm.red[r][tid];
                st_ll(&g_qpart[h][split][tid], s, tag);
                u64 w[NSPLIT];
                int spins = 0;
                for (;;) {
                    bool ok = true;
#pragma unroll
                    for (int i = 0; i < NSPLIT; i++) w[i] = ld_ll(&g_qpart[h][i][tid]);
#pragma unroll
                    for (int i = 0; i < NSPLIT; i++) ok = ok && ll_ok(w[i], tag);
                    if (ok || ++spins > SPIN_LIMIT) break;
                }
                sm.q[tid] = bf16r((ll_val(w[0]) + ll_val(w[1])) + (ll_val(w[2]) + ll_val(w[3])));
            }
            named_bar_sync(1, NCONS);
        }
        DBG_STAMP(1);

        const int half = lane >> 4;
        const int l16  = lane & 15;
        float qf[8];
#pragma unroll
        for (int j = 0; j < 8; j++) qf[j] = sm.q[l16 * 8 + j];

        float m = -INFINITY, l = 0.f;
        float o[8];
#pragma unroll
        for (int j = 0; j < 8; j++) o[j] = 0.f;
        const float scale = 0.08838834764831845f;
        const int row_off = (wid * (2 * NR) + half) * (DH * 2) + l16 * 16;

        int s = 0;
        uint32_t ph = 0;
#pragma unroll 1
        for (;;) {
            mbar_wait(&sm.full_k[s], ph);
            if (*reinterpret_cast<volatile int*>(&sm.valid[s]) == 0) break;
            uint4 kk[NR];
#pragma unroll
            for (int i = 0; i < NR; i++) kk[i] = lds128(sm.kbuf[s] + row_off + i * 2 * (DH * 2));
            float sc[NR];
#pragma unroll
            for (int i = 0; i < NR; i++) {
                float a = qf[0] * bf_lo(kk[i].x);
                a = fmaf(qf[1], bf_hi(kk[i].x), a);
                a = fmaf(qf[2], bf_lo(kk[i].y), a);
                a = fmaf(qf[3], bf_hi(kk[i].y), a);
                a = fmaf(qf[4], bf_lo(kk[i].z), a);
                a = fmaf(qf[5], bf_hi(kk[i].z), a);
                a = fmaf(qf[6], bf_lo(kk[i].w), a);
                a = fmaf(qf[7], bf_hi(kk[i].w), a);
                sc[i] = a;
            }
#pragma unroll
            for (int off = 8; off > 0; off >>= 1) {
#pragma unroll
                for (int i = 0; i < NR; i++) sc[i] += __shfl_xor_sync(0xffffffffu, sc[i], off);
            }
#pragma unroll
            for (int i = 0; i < NR; i++) sc[i] = bf16r(bf16r(sc[i]) * scale);
            float mnew = m;
#pragma unroll
            for (int i = 0; i < NR; i++) mnew = fmaxf(mnew, sc[i]);
            const float corr = exp2f((m - mnew) * LOG2E);
            float p[NR];
            float ps = 0.f;
#pragma unroll
            for (int i = 0; i < NR; i++) {
                p[i] = exp2f((sc[i] - mnew) * LOG2E);
                ps += p[i];
            }
            l = l * corr + ps;
            m = mnew;
#pragma unroll
            for (int j = 0; j < 8; j++) o[j] *= corr;

            mbar_wait(&sm.full_v[s], ph);
            uint4 vv[NR];
#pragma unroll
            for (int i = 0; i < NR; i++) vv[i] = lds128(sm.vbuf[s] + row_off + i * 2 * (DH * 2));
#pragma unroll
            for (int i = 0; i < NR; i++) fma8(o, p[i], vv[i]);
            __syncwarp();
            if (lane == 0) mbar_arrive(&sm.empty[s]);
            if (++s == NSTAGE) { s = 0; ph ^= 1; }
        }
        DBG_STAMP(2);

        {
            const int st = wid * 2 + half;
#pragma unroll
            for (int j = 0; j < 8; j++) sm.red[st][l16 * 8 + j] = o[j];
            if (l16 == 0) {
                sm.ms[st] = m;
                sm.ls[st] = l;
            }
            named_bar_sync(1, NCONS);
            if (tid < DH) {
                float M = sm.ms[0];
#pragma unroll
                for (int i = 1; i < 16; i++) M = fmaxf(M, sm.ms[i]);
                float L = 0.f, O = 0.f;
                if (M > -INFINITY) {
#pragma unroll
                    for (int i = 0; i < 16; i++) {
                        const float w = exp2f((sm.ms[i] - M) * LOG2E);
                        L += w * sm.ls[i];
                        O += w * sm.red[i][tid];
                    }
                }
                st_ll(&g_part[h][split][tid], O, tag);
                if (tid == 0) {
                    st_ll(&g_part[h][split][DH], M, tag);
                    st_ll(&g_part[h][split][DH + 1], L, tag);
                }
                u64 wo_[NSPLIT], wm[NSPLIT], wl[NSPLIT];
                int spins = 0;
                for (;;) {
                    bool ok = true;
#pragma unroll
                    for (int i = 0; i < NSPLIT; i++) {
                        wo_[i] = ld_ll(&g_part[h][i][tid]);
                        ld_ll2(&g_part[h][i][DH], wm[i], wl[i]);
                    }
#pragma unroll
                    for (int i = 0; i < NSPLIT; i++) ok = ok && ll_ok(wo_[i], tag) && ll_ok(wm[i], tag) && ll_ok(wl[i], tag);
                    if (ok || ++spins > SPIN_LIMIT) break;
                }
                float MM = -INFINITY;
#pragma unroll
                for (int i = 0; i < NSPLIT; i++) MM = fmaxf(MM, ll_val(wm[i]));
                float LL = 0.f, OO = 0.f;
#pragma unroll
                for (int i = 0; i < NSPLIT; i++) {
                    const float mi = ll_val(wm[i]);
                    const float w  = (mi > -INFINITY) ? exp2f((mi - MM) * LOG2E) : 0.f;
                    LL += w * ll_val(wl[i]);
                    OO += w * ll_val(wo_[i]);
                }
                sm.of[tid] = bf16r(OO / LL);
            }
            named_bar_sync(1, NCONS);
        }
        DBG_STAMP(7);

        {
            if (rgo < 12) {
                float acc[8];
#pragma unroll
                for (int j = 0; j < 8; j++) acc[j] = 0.f;
#pragma unroll
                for (int u = 0; u < 11; u++) {
                    const int row = rgo + 12 * u;
                    if (u < 10 || row < DH) fma8(acc, sm.of[row], wor[u]);
                }
#pragma unroll
                for (int j = 0; j < 8; j++) sm.red[rgo][cgo * 8 + j] = acc[j];
            }
            named_bar_sync(1, NCONS);
            if (tid < OCOLS) {
                float a = 0.f;
#pragma unroll
                for (int r = 0; r < 12; r++) a += sm.red[r][tid];
                st_ll(&g_headout[h][split * OCOLS + tid], a, tag);
            }
        }
        DBG_STAMP(3);
        return;
    }

    {
        const int mc = cta - N_ATTN_CTA;
        for (int i = tid; i < D_MODEL; i += NTHREADS) sm.xn[i] = __bfloat162float(x[i]);
        named_bar_sync(1, NTHREADS);
        layernorm_bf16(sm.xn, sm.xn, &sm.red[0][0], tid, NTHREADS, 1);
        layernorm_bf16(sm.xn, sm.xn, &sm.red[0][0], tid, NTHREADS, 1);

        constexpr int CPC = FF / N_MLP_CTA;
        float* hs = reinterpret_cast<float*>(sm.vbuf);
        {
            constexpr int NCG = CPC / 8;
            constexpr int NRG = 5;
            const int cg = tid % NCG, rg = tid / NCG;
            if (rg < NRG) {
                float acc[8];
#pragma unroll
                for (int j = 0; j < 8; j++) acc[j] = 0.f;
                const uint8_t* wbase = reinterpret_cast<const uint8_t*>(w1) + (size_t)(mc * CPC + cg * 8) * 2;
#pragma unroll 1
                for (int it = 0; it < 8; it++) {
                    uint4 w[16];
#pragma unroll
                    for (int u = 0; u < 16; u++) w[u] = ldg_nc(wbase + (size_t)(rg * 128 + it * 16 + u) * (FF * 2));
#pragma unroll
                    for (int u = 0; u < 16; u++) fma8(acc, sm.xn[rg * 128 + it * 16 + u], w[u]);
                }
#pragma unroll
                for (int j = 0; j < 8; j++) sm.red2[rg][cg * 8 + j] = acc[j];
            }
            __syncthreads();
            for (int c = tid; c < CPC; c += NTHREADS) {
                float s = 0.f;
#pragma unroll
                for (int r = 0; r < NRG; r++) s += sm.red2[r][c];
                const int f = mc * CPC + c;
                float u = bf16r(bf16r(s) + __bfloat162float(b1[f]));
                hs[c] = bf16r(gelu_tanh(u));
            }
            __syncthreads();
        }
        DBG_STAMP(1);
        {
            const int cg = tid % 80, rgp = tid / 80;
            if (rgp < 3) {
                float acc[8];
#pragma unroll
                for (int j = 0; j < 8; j++) acc[j] = 0.f;
                const uint8_t* wbase = reinterpret_cast<const uint8_t*>(w2) + (size_t)(mc * CPC) * (D_MODEL * 2) + cg * 16;
#pragma unroll 1
                for (int it = 0; it < 9; it++) {
                    uint4 w[16];
#pragma unroll
                    for (int u = 0; u < 16; u++) w[u] = ldg_nc(wbase + (size_t)(rgp * 144 + it * 16 + u) * (D_MODEL * 2));
#pragma unroll
                    for (int u = 0; u < 16; u++) fma8(acc, hs[rgp * 144 + it * 16 + u], w[u]);
                }
#pragma unroll
                for (int j = 0; j < 8; j++) sm.red2[rgp][cg * 8 + j] = acc[j];
            }
            __syncthreads();
            for (int n = tid; n < D_MODEL; n += NTHREADS)
                st_ll(&g_mlp_part[mc][n], sm.red2[0][n] + sm.red2[1][n] + sm.red2[2][n], tag);
        }
        DBG_STAMP(2);
        if (mc != 0) return;

        if (tid < D_MODEL / 4) {
            const int n0 = tid * 4;
            int spins = 0;
            float a[4] = {0.f, 0.f, 0.f, 0.f}, z[4] = {0.f, 0.f, 0.f, 0.f};
            {
                u64 zw[N_MLP_CTA][4];
                for (;;) {
                    bool ok = true;
#pragma unroll
                    for (int c = 0; c < N_MLP_CTA; c++) {
                        ld_ll2(&g_mlp_part[c][n0], zw[c][0], zw[c][1]);
                        ld_ll2(&g_mlp_part[c][n0 + 2], zw[c][2], zw[c][3]);
                    }
#pragma unroll
                    for (int c = 0; c < N_MLP_CTA; c++)
#pragma unroll
                        for (int j = 0; j < 4; j++) ok = ok && ll_ok(zw[c][j], tag);
                    if (ok || ++spins > SPIN_LIMIT) break;
                    __nanosleep(200);
                }
#pragma unroll
                for (int c = 0; c < N_MLP_CTA; c++)
#pragma unroll
                    for (int j = 0; j < 4; j++) z[j] += ll_val(zw[c][j]);
            }
            while (!ll_ok(ld_ll(&g_headout[0][n0]), tag) && ++spins < SPIN_LIMIT) __nanosleep(100);
#pragma unroll 1
            for (int hb = 0; hb < NHEAD; hb += 16) {
                u64 hw[16][4];
                for (;;) {
                    bool ok = true;
#pragma unroll
                    for (int hh = 0; hh < 16; hh++) {
                        ld_ll2(&g_headout[hb + hh][n0], hw[hh][0], hw[hh][1]);
                        ld_ll2(&g_headout[hb + hh][n0 + 2], hw[hh][2], hw[hh][3]);
                    }
#pragma unroll
                    for (int hh = 0; hh < 16; hh++)
#pragma unroll
                        for (int j = 0; j < 4; j++) ok = ok && ll_ok(hw[hh][j], tag);
                    if (ok || ++spins > SPIN_LIMIT) break;
                }
#pragma unroll
                for (int hh = 0; hh < 16; hh++)
#pragma unroll
                    for (int j = 0; j < 4; j++) a[j] += ll_val(hw[hh][j]);
            }
#pragma unroll
            for (int j = 0; j < 4; j++) {
                const int n = n0 + j;
                const float t  = bf16r(__bfloat162float(x[n]) + bf16r(a[j]));
                const float zz = bf16r(bf16r(z[j]) + __bfloat162float(b2[n]));
                out[n] = __float2bfloat16_rn(t + zz);
            }
        }
        __syncthreads();
        if (tid == 0) *reinterpret_cast<volatile unsigned*>(&g_epoch) = epoch + 1u;
        DBG_STAMP(3);
    }
}

}

extern "C" void kernel_launch(void* const* d_in, const int* in_sizes, int n_in, void* d_out, int out_size) {
    const __nv_bfloat16* x  = (const __nv_bfloat16*)d_in[0];
    const __nv_bfloat16* kc = (const __nv_bfloat16*)d_in[1];
    const __nv_bfloat16* vc = (const __nv_bfloat16*)d_in[2];
    const __nv_bfloat16* wq = (const __nv_bfloat16*)d_in[3];
    const __nv_bfloat16* wo = (const __nv_bfloat16*)d_in[4];
    const __nv_bfloat16* w1 = (const __nv_bfloat16*)d_in[6];
    const __nv_bfloat16* b1 = (const __nv_bfloat16*)d_in[7];
    const __nv_bfloat16* w2 = (const __nv_bfloat16*)d_in[8];
    const __nv_bfloat16* b2 = (const __nv_bfloat16*)d_in[9];
    __nv_bfloat16* out = (__nv_bfloat16*)d_out;

    static bool attr_set = false;
    if (!attr_set) {
        cudaFuncSetAttribute(fused_decode_kernel, cudaFuncAttributeMaxDynamicSharedMemorySize, (int)sizeof(SmemLayout));
        attr_set = true;
    }
    fused_decode_kernel<<<GRID, NTHREADS, sizeof(SmemLayout)>>>(x, kc, vc, wq, wo, w1, b1, w2, b2, out);
}
```

```cpp
#include <cuda_runtime.h>
#include <cuda_bf16.h>
#include <stdint.h>

namespace {

constexpr int D_MODEL = 640;
constexpr int NHEAD   = 32;
constexpr int DH      = 128;
constexpr int SK      = 16384;
constexpr int FF      = 1728;

#define CFG_TILE 64
#define CFG_NSTAGE 6
#define CFG_DEPTH 3

constexpr int NSPLIT        = 4;
constexpr int TILE          = CFG_TILE;
constexpr int NSTAGE        = CFG_NSTAGE;
constexpr int DEPTH         = CFG_DEPTH;
constexpr int NT_HEAD       = SK / TILE;
constexpr int TILE_BYTES    = TILE * DH * 2;
constexpr int NCONS_WARPS   = 8;
constexpr int NCONS         = NCONS_WARPS * 32;
constexpr int NR            = TILE / NCONS_WARPS / 2;
constexpr int NTHREADS      = NCONS + 32;
constexpr int N_ATTN_CTA    = NHEAD * NSPLIT;
constexpr int N_MLP_CTA     = 4;
constexpr int GRID          = N_ATTN_CTA + N_MLP_CTA;
constexpr int OCOLS         = D_MODEL / NSPLIT;
constexpr int SPIN_LIMIT    = 1 << 22;

constexpr float LOG2E = 1.4426950408889634f;

typedef unsigned long long u64;

__device__ __align__(16) u64 g_qpart[NHEAD][NSPLIT][DH];
__device__ __align__(16) u64 g_part[NHEAD][NSPLIT][DH + 2];
__device__ __align__(16) u64 g_headout[NHEAD][D_MODEL];
__device__ __align__(16) u64 g_mlp_part[N_MLP_CTA][D_MODEL];
__device__ unsigned g_ticket[NHEAD];
__device__ unsigned g_epoch;

#define DBG_STAMP(i) do { } while (0)

struct __align__(128) SmemLayout {
    uint8_t  kbuf[NSTAGE][TILE_BYTES];
    uint8_t  vbuf[NSTAGE][TILE_BYTES];
    uint64_t full_k[NSTAGE];
    uint64_t full_v[NSTAGE];
    uint64_t empty[NSTAGE];
    int      valid[NSTAGE];
    float    xn[D_MODEL];
    float    q[DH];
    float    red[16][OCOLS];
    float    ms[16];
    float    ls[16];
    float    of[DH];
    __align__(16) float red2[5][D_MODEL];
};

__device__ __forceinline__ float bf16r(float x) { return __bfloat162float(__float2bfloat16_rn(x)); }
__device__ __forceinline__ float bf_lo(uint32_t u) { return __uint_as_float(u << 16); }
__device__ __forceinline__ float bf_hi(uint32_t u) { return __uint_as_float(u & 0xffff0000u); }

__device__ __forceinline__ uint32_t smem_u32(const void* p) { return (uint32_t)__cvta_generic_to_shared(p); }
__device__ __forceinline__ void mbar_init(uint64_t* bar, uint32_t count) {
    asm volatile("mbarrier.init.shared::cta.b64 [%0], %1;" ::"r"(smem_u32(bar)), "r"(count) : "memory");
}
__device__ __forceinline__ void mbar_expect_tx(uint64_t* bar, uint32_t bytes) {
    asm volatile("mbarrier.arrive.expect_tx.shared::cta.b64 _, [%0], %1;" ::"r"(smem_u32(bar)), "r"(bytes) : "memory");
}
__device__ __forceinline__ void mbar_arrive(uint64_t* bar) {
    asm volatile("mbarrier.arrive.shared::cta.b64 _, [%0];" ::"r"(smem_u32(bar)) : "memory");
}
__device__ __forceinline__ bool mbar_try_wait(uint64_t* bar, uint32_t parity) {
    uint32_t ok;
    asm volatile(
        "{\n\t.reg .pred p;\n\t"
        "mbarrier.try_wait.parity.shared::cta.b64 p, [%1], %2;\n\t"
        "selp.u32 %0, 1, 0, p;\n\t}"
        : "=r"(ok)
        : "r"(smem_u32(bar)), "r"(parity)
        : "memory");
    return ok != 0;
}
__device__ __forceinline__ void mbar_wait(uint64_t* bar, uint32_t parity) {
    while (!mbar_try_wait(bar, parity)) {
    }
}
__device__ __forceinline__ void bulk_g2s(void* dst, const void* src, uint32_t bytes, uint64_t* bar, uint64_t policy) {
    asm volatile(
        "cp.async.bulk.shared::cluster.global.mbarrier::complete_tx::bytes.L2::cache_hint [%0], [%1], %2, [%3], %4;"
        ::"r"(smem_u32(dst)), "l"(src), "r"(bytes), "r"(smem_u32(bar)), "l"(policy)
        : "memory");
}
__device__ __forceinline__ uint4 ldg_nc(const void* p) {
    uint4 r;
    asm volatile("ld.global.nc.L1::no_allocate.v4.u32 {%0,%1,%2,%3}, [%4];"
                 : "=r"(r.x), "=r"(r.y), "=r"(r.z), "=r"(r.w)
                 : "l"(p));
    return r;
}
__device__ __forceinline__ uint4 lds128(const void* p) {
    uint4 r;
    asm volatile("ld.shared.v4.u32 {%0,%1,%2,%3}, [%4];"
                 : "=r"(r.x), "=r"(r.y), "=r"(r.z), "=r"(r.w)
                 : "r"(smem_u32(p)));
    return r;
}
__device__ __forceinline__ void named_bar_sync(int id, int n) {
    asm volatile("bar.sync %0, %1;" ::"r"(id), "r"(n) : "memory");
}
__device__ __forceinline__ void st_ll(u64* p, float v, unsigned tag) {
    const u64 w = ((u64)tag << 32) | (u64)__float_as_uint(v);
    asm volatile("st.relaxed.gpu.global.b64 [%0], %1;" ::"l"(p), "l"(w) : "memory");
}
__device__ __forceinline__ u64 ld_ll(const u64* p) {
    u64 w;
    asm volatile("ld.relaxed.gpu.global.b64 %0, [%1];" : "=l"(w) : "l"(p) : "memory");
    return w;
}
__device__ __forceinline__ void ld_ll2(const u64* p, u64& a, u64& b) {
    asm volatile("ld.relaxed.gpu.global.v2.b64 {%0,%1}, [%2];" : "=l"(a), "=l"(b) : "l"(p) : "memory");
}
__device__ __forceinline__ bool ll_ok(u64 w, unsigned tag) { return (unsigned)(w >> 32) == tag; }
__device__ __forceinline__ float ll_val(u64 w) { return __uint_as_float((unsigned)w); }

__device__ __forceinline__ void fma8(float* acc, float xv, const uint4& w) {
    acc[0] = fmaf(xv, bf_lo(w.x), acc[0]); acc[1] = fmaf(xv, bf_hi(w.x), acc[1]);
    acc[2] = fmaf(xv, bf_lo(w.y), acc[2]); acc[3] = fmaf(xv, bf_hi(w.y), acc[3]);
    acc[4] = fmaf(xv, bf_lo(w.z), acc[4]); acc[5] = fmaf(xv, bf_hi(w.z), acc[5]);
    acc[6] = fmaf(xv, bf_lo(w.w), acc[6]); acc[7] = fmaf(xv, bf_hi(w.w), acc[7]);
}

__device__ void layernorm_bf16(const float* in, float* out, float* scr, int tid, int nthr, int bar_id) {
    const int lane = tid & 31, wid = tid >> 5, nw = nthr >> 5;
    float s = 0.f;
    for (int i = tid; i < D_MODEL; i += nthr) s += in[i];
#pragma unroll
    for (int o = 16; o > 0; o >>= 1) s += __shfl_xor_sync(0xffffffffu, s, o);
    if (lane == 0) scr[wid] = s;
    named_bar_sync(bar_id, nthr);
    float tot = 0.f;
    for (int w = 0; w < nw; w++) tot += scr[w];
    const float mean = tot * (1.0f / D_MODEL);
    float vs = 0.f;
    for (int i = tid; i < D_MODEL; i += nthr) {
        float d = in[i] - mean;
        vs += d * d;
    }
#pragma unroll
    for (int o = 16; o > 0; o >>= 1) vs += __shfl_xor_sync(0xffffffffu, vs, o);
    if (lane == 0) scr[32 + wid] = vs;
    named_bar_sync(bar_id, nthr);
    float vtot = 0.f;
    for (int w = 0; w < nw; w++) vtot += scr[32 + w];
    const float m_b = bf16r(mean);
    const float v_b = bf16r(vtot * (1.0f / D_MODEL));
    const float den = bf16r(sqrtf(bf16r(v_b + 1e-5f)));
    for (int i = tid; i < D_MODEL; i += nthr) {
        float d = bf16r(in[i] - m_b);
        out[i]  = bf16r(d / den);
    }
    named_bar_sync(bar_id, nthr);
}

__device__ __forceinline__ float gelu_tanh(float x) {
    const float k0 = 0.7978845608028654f, k1 = 0.044715f;
    float inner = k0 * (x + k1 * x * x * x);
    return 0.5f * x * (1.0f + tanhf(inner));
}

__global__ void __launch_bounds__(NTHREADS, 1)
fused_decode_kernel(const __nv_bfloat16* __restrict__ x,
                    const __nv_bfloat16* __restrict__ kc,
                    const __nv_bfloat16* __restrict__ vc,
                    const __nv_bfloat16* __restrict__ wq,
                    const __nv_bfloat16* __restrict__ wo,
                    const __nv_bfloat16* __restrict__ w1,
                    const __nv_bfloat16* __restrict__ b1,
                    const __nv_bfloat16* __restrict__ w2,
                    const __nv_bfloat16* __restrict__ b2,
                    __nv_bfloat16* __restrict__ out) {
    extern __shared__ uint8_t smem_raw[];
    SmemLayout& sm = *reinterpret_cast<SmemLayout*>(smem_raw);
    const int tid  = threadIdx.x;
    const int lane = tid & 31;
    const int wid  = tid >> 5;
    const int cta  = blockIdx.x;
    DBG_STAMP(0);

    const unsigned epoch = *reinterpret_cast<volatile unsigned*>(&g_epoch);
    const unsigned tag   = epoch + 1u;

    if (cta < N_ATTN_CTA) {
        const int h     = cta % NHEAD;
        const int split = cta / NHEAD;

        const uint8_t* kbase = reinterpret_cast<const uint8_t*>(kc) + (size_t)h * SK * (DH * 2);
        const uint8_t* vbase = reinterpret_cast<const uint8_t*>(vc) + (size_t)h * SK * (DH * 2);
        uint64_t policy = 0;
        if (tid == NCONS) {
            asm volatile("createpolicy.fractional.L2::evict_first.b64 %0, 1.0;" : "=l"(policy));
#pragma unroll
            for (int s = 0; s < NSTAGE; s++) {
                mbar_init(&sm.full_k[s], 1);
                mbar_init(&sm.full_v[s], 1);
                mbar_init(&sm.empty[s], NCONS_WARPS);
            }
            asm volatile("fence.mbarrier_init.release.cluster;" ::: "memory");
#pragma unroll
            for (int s = 0; s < NSTAGE; s++) {
                const int t = split + NSPLIT * s;
                sm.valid[s] = 1;
                mbar_expect_tx(&sm.full_k[s], TILE_BYTES);
                bulk_g2s(sm.kbuf[s], kbase + (size_t)t * TILE_BYTES, TILE_BYTES, &sm.full_k[s], policy);
                mbar_expect_tx(&sm.full_v[s], TILE_BYTES);
                bulk_g2s(sm.vbuf[s], vbase + (size_t)t * TILE_BYTES, TILE_BYTES, &sm.full_v[s], policy);
            }
        }

        const int l16q = tid & 15;
        const int rgq  = tid >> 4;
        uint4 wqr[10];
        const int cgo = tid % 20;
        const int rgo = tid / 20;
        uint4 wor[11];
        if (wid < NCONS_WARPS) {
            const uint8_t* wbase = reinterpret_cast<const uint8_t*>(wq) + (size_t)h * DH * 2 + l16q * 16;
#pragma unroll
            for (int u = 0; u < 10; u++)
                wqr[u] = ldg_nc(wbase + (size_t)(split * 160 + rgq + 16 * u) * (NHEAD * DH * 2));
        }
        __syncthreads();

        if (wid == NCONS_WARPS) {
            if (lane == 0) {
                constexpr unsigned NSTATIC = NSTAGE * NSPLIT;
                const unsigned tbase = epoch * (unsigned)(NT_HEAD - NSTATIC + NSPLIT) - NSTATIC;
                unsigned next = atomicAdd(&g_ticket[h], 1u) - tbase;
                for (int it = NSTAGE;; it++) {
                    const int s = it % NSTAGE;
                    const unsigned t = next;
                    if (t < (unsigned)NT_HEAD) next = atomicAdd(&g_ticket[h], 1u) - tbase;
                    const int d = it - DEPTH;
                    mbar_wait(&sm.empty[d % NSTAGE], (d / NSTAGE) & 1);
                    if (t >= (unsigned)NT_HEAD) {
                        sm.valid[s] = 0;
                        mbar_arrive(&sm.full_k[s]);
                        break;
                    }
                    sm.valid[s] = 1;
                    mbar_expect_tx(&sm.full_k[s], TILE_BYTES);
                    bulk_g2s(sm.kbuf[s], kbase + (size_t)t * TILE_BYTES, TILE_BYTES, &sm.full_k[s], policy);
                    mbar_expect_tx(&sm.full_v[s], TILE_BYTES);
                    bulk_g2s(sm.vbuf[s], vbase + (size_t)t * TILE_BYTES, TILE_BYTES, &sm.full_v[s], policy);
                }
            }
            return;
        }

        if (rgo < 12) {
            const uint8_t* wbase = reinterpret_cast<const uint8_t*>(wo) + (size_t)h * DH * (D_MODEL * 2) + split * (OCOLS * 2) + cgo * 16;
#pragma unroll
            for (int u = 0; u < 11; u++) {
                const int row = rgo + 12 * u;
                if (u < 10 || row < DH) wor[u] = ldg_nc(wbase + (size_t)row * (D_MODEL * 2));
            }
        }

        for (int i = tid; i < D_MODEL; i += NCONS) sm.xn[i] = __bfloat162float(x[i]);
        named_bar_sync(1, NCONS);
        layernorm_bf16(sm.xn, sm.xn, &sm.red[0][0], tid, NCONS, 1);
        DBG_STAMP(4);

        {
            float acc[8];
#pragma unroll
            for (int j = 0; j < 8; j++) acc[j] = 0.f;
#pragma unroll
            for (int u = 0; u < 10; u++) fma8(acc, sm.xn[split * 160 + rgq + 16 * u], wqr[u]);
#pragma unroll
            for (int j = 0; j < 8; j++) sm.red[rgq][l16q * 8 + j] = acc[j];
            DBG_STAMP(5);
            named_bar_sync(1, NCONS);
            if (tid < DH) {
                float s = 0.f;
#pragma unroll
                for (int r = 0; r < 16; r++) s += sm.red[r][tid];
                st_ll(&g_qpart[h][split][tid], s, tag);
                u64 w[NSPLIT];
                int spins = 0;
                for (;;) {
                    bool ok = true;
#pragma unroll
                    for (int i = 0; i < NSPLIT; i++) w[i] = ld_ll(&g_qpart[h][i][tid]);
#pragma unroll
                    for (int i = 0; i < NSPLIT; i++) ok = ok && ll_ok(w[i], tag);
                    if (ok || ++spins > SPIN_LIMIT) break;
                }
                sm.q[tid] = bf16r((ll_val(w[0]) + ll_val(w[1])) + (ll_val(w[2]) + ll_val(w[3])));
            }
            named_bar_sync(1, NCONS);
        }
        DBG_STAMP(1);

        const int half = lane >> 4;
        const int l16  = lane & 15;
        float qf[8];
#pragma unroll
        for (int j = 0; j < 8; j++) qf[j] = sm.q[l16 * 8 + j];

        float m = -INFINITY, l = 0.f;
        float o[8];
#pragma unroll
        for (int j = 0; j < 8; j++) o[j] = 0.f;
        const float scale = 0.08838834764831845f;
        const int row_off = (wid * (2 * NR) + half) * (DH * 2) + l16 * 16;

        int s = 0;
        uint32_t ph = 0;
#pragma unroll 1
        for (;;) {
            mbar_wait(&sm.full_k[s], ph);
            if (*reinterpret_cast<volatile int*>(&sm.valid[s]) == 0) break;
            uint4 kk[NR];
#pragma unroll
            for (int i = 0; i < NR; i++) kk[i] = lds128(sm.kbuf[s] + row_off + i * 2 * (DH * 2));
            float sc[NR];
#pragma unroll
            for (int i = 0; i < NR; i++) {
                float a = qf[0] * bf_lo(kk[i].x);
                a = fmaf(qf[1], bf_hi(kk[i].x), a);
                a = fmaf(qf[2], bf_lo(kk[i].y), a);
                a = fmaf(qf[3], bf_hi(kk[i].y), a);
                a = fmaf(qf[4], bf_lo(kk[i].z), a);
                a = fmaf(qf[5], bf_hi(kk[i].z), a);
                a = fmaf(qf[6], bf_lo(kk[i].w), a);
                a = fmaf(qf[7], bf_hi(kk[i].w), a);
                sc[i] = a;
            }
#pragma unroll
            for (int off = 8; off > 0; off >>= 1) {
#pragma unroll
                for (int i = 0; i < NR; i++) sc[i] += __shfl_xor_sync(0xffffffffu, sc[i], off);
            }
#pragma unroll
            for (int i = 0; i < NR; i++) sc[i] = bf16r(bf16r(sc[i]) * scale);
            float mnew = m;
#pragma unroll
            for (int i = 0; i < NR; i++) mnew = fmaxf(mnew, sc[i]);
            const float corr = exp2f((m - mnew) * LOG2E);
            float p[NR];
            float ps = 0.f;
#pragma unroll
            for (int i = 0; i < NR; i++) {
                p[i] = exp2f((sc[i] - mnew) * LOG2E);
                ps += p[i];
            }
            l = l * corr + ps;
            m = mnew;
#pragma unroll
            for (int j = 0; j < 8; j++) o[j] *= corr;

            mbar_wait(&sm.full_v[s], ph);
            uint4 vv[NR];
#pragma unroll
            for (int i = 0; i < NR; i++) vv[i] = lds128(sm.vbuf[s] + row_off + i * 2 * (DH * 2));
#pragma unroll
            for (int i = 0; i < NR; i++) fma8(o, p[i], vv[i]);
            __syncwarp();
            if (lane == 0) mbar_arrive(&sm.empty[s]);
            if (++s == NSTAGE) { s = 0; ph ^= 1; }
        }
        DBG_STAMP(2);

        {
            const int st = wid * 2 + half;
#pragma unroll
            for (int j = 0; j < 8; j++) sm.red[st][l16 * 8 + j] = o[j];
            if (l16 == 0) {
                sm.ms[st] = m;
                sm.ls[st] = l;
            }
            named_bar_sync(1, NCONS);
            if (tid < DH) {
                float M = sm.ms[0];
#pragma unroll
                for (int i = 1; i < 16; i++) M = fmaxf(M, sm.ms[i]);
                float L = 0.f, O = 0.f;
                if (M > -INFINITY) {
#pragma unroll
                    for (int i = 0; i < 16; i++) {
                        const float w = exp2f((sm.ms[i] - M) * LOG2E);
                        L += w * sm.ls[i];
                        O += w * sm.red[i][tid];
                    }
                }
                st_ll(&g_part[h][split][tid], O, tag);
                if (tid == 0) {
                    st_ll(&g_part[h][split][DH], M, tag);
                    st_ll(&g_part[h][split][DH + 1], L, tag);
                }
                u64 wo_[NSPLIT], wm[NSPLIT], wl[NSPLIT];
                int spins = 0;
                for (;;) {
                    bool ok = true;
#pragma unroll
                    for (int i = 0; i < NSPLIT; i++) {
                        wo_[i] = ld_ll(&g_part[h][i][tid]);
                        ld_ll2(&g_part[h][i][DH], wm[i], wl[i]);
                    }
#pragma unroll
                    for (int i = 0; i < NSPLIT; i++) ok = ok && ll_ok(wo_[i], tag) && ll_ok(wm[i], tag) && ll_ok(wl[i], tag);
                    if (ok || ++spins > SPIN_LIMIT) break;
                }
                float MM = -INFINITY;
#pragma unroll
                for (int i = 0; i < NSPLIT; i++) MM = fmaxf(MM, ll_val(wm[i]));
                float LL = 0.f, OO = 0.f;
#pragma unroll
                for (int i = 0; i < NSPLIT; i++) {
                    const float mi = ll_val(wm[i]);
                    const float w  = (mi > -INFINITY) ? exp2f((mi - MM) * LOG2E) : 0.f;
                    LL += w * ll_val(wl[i]);
                    OO += w * ll_val(wo_[i]);
                }
                sm.of[tid] = bf16r(OO / LL);
            }
            named_bar_sync(1, NCONS);
        }
        DBG_STAMP(7);

        {
            if (rgo < 12) {
                float acc[8];
#pragma unroll
                for (int j = 0; j < 8; j++) acc[j] = 0.f;
#pragma unroll
                for (int u = 0; u < 11; u++) {
                    const int row = rgo + 12 * u;
                    if (u < 10 || row < DH) fma8(acc, sm.of[row], wor[u]);
                }
#pragma unroll
                for (int j = 0; j < 8; j++) sm.red[rgo][cgo * 8 + j] = acc[j];
            }
            named_bar_sync(1, NCONS);
            if (tid < OCOLS) {
                float a = 0.f;
#pragma unroll
                for (int r = 0; r < 12; r++) a += sm.red[r][tid];
                st_ll(&g_headout[h][split * OCOLS + tid], a, tag);
            }
        }
        DBG_STAMP(3);
        return;
    }

    {
        const int mc = cta - N_ATTN_CTA;
        for (int i = tid; i < D_MODEL; i += NTHREADS) sm.xn[i] = __bfloat162float(x[i]);
        named_bar_sync(1, NTHREADS);
        layernorm_bf16(sm.xn, sm.xn, &sm.red[0][0], tid, NTHREADS, 1);
        layernorm_bf16(sm.xn, sm.xn, &sm.red[0][0], tid, NTHREADS, 1);

        constexpr int CPC = FF / N_MLP_CTA;
        float* hs = reinterpret_cast<float*>(sm.vbuf);
        {
            constexpr int NCG = CPC / 8;
            constexpr int NRG = 5;
            const int cg = tid % NCG, rg = tid / NCG;
            if (rg < NRG) {
                float acc[8];
#pragma unroll
                for (int j = 0; j < 8; j++) acc[j] = 0.f;
                const uint8_t* wbase = reinterpret_cast<const uint8_t*>(w1) + (size_t)(mc * CPC + cg * 8) * 2;
#pragma unroll 1
                for (int it = 0; it < 8; it++) {
                    uint4 w[16];
#pragma unroll
                    for (int u = 0; u < 16; u++) w[u] = ldg_nc(wbase + (size_t)(rg * 128 + it * 16 + u) * (FF * 2));
#pragma unroll
                    for (int u = 0; u < 16; u++) fma8(acc, sm.xn[rg * 128 + it * 16 + u], w[u]);
                }
#pragma unroll
                for (int j = 0; j < 8; j++) sm.red2[rg][cg * 8 + j] = acc[j];
            }
            __syncthreads();
            for (int c = tid; c < CPC; c += NTHREADS) {
                float s = 0.f;
#pragma unroll
                for (int r = 0; r < NRG; r++) s += sm.red2[r][c];
                const int f = mc * CPC + c;
                float u = bf16r(bf16r(s) + __bfloat162float(b1[f]));
                hs[c] = bf16r(gelu_tanh(u));
            }
            __syncthreads();
        }
        DBG_STAMP(1);
        {
            const int cg = tid % 80, rgp = tid / 80;
            if (rgp < 3) {
                float acc[8];
#pragma unroll
                for (int j = 0; j < 8; j++) acc[j] = 0.f;
                const uint8_t* wbase = reinterpret_cast<const uint8_t*>(w2) + (size_t)(mc * CPC) * (D_MODEL * 2) + cg * 16;
#pragma unroll 1
                for (int it = 0; it < 9; it++) {
                    uint4 w[16];
#pragma unroll
                    for (int u = 0; u < 16; u++) w[u] = ldg_nc(wbase + (size_t)(rgp * 144 + it * 16 + u) * (D_MODEL * 2));
#pragma unroll
                    for (int u = 0; u < 16; u++) fma8(acc, hs[rgp * 144 + it * 16 + u], w[u]);
                }
#pragma unroll
                for (int j = 0; j < 8; j++) sm.red2[rgp][cg * 8 + j] = acc[j];
            }
            __syncthreads();
            for (int n = tid; n < D_MODEL; n += NTHREADS)
                st_ll(&g_mlp_part[mc][n], sm.red2[0][n] + sm.red2[1][n] + sm.red2[2][n], tag);
        }
        DBG_STAMP(2);

        {
            const int cp = tid % 80, hg = tid / 80;
            const int n0 = mc * OCOLS + cp * 2;
            float a0 = 0.f, a1 = 0.f;
            int spins = 0;
            if (hg < 2) {
                while (!ll_ok(ld_ll(&g_headout[hg * 16][n0]), tag) && ++spins < SPIN_LIMIT) __nanosleep(100);
                u64 hw[16][2];
                for (;;) {
                    bool ok = true;
#pragma unroll
                    for (int hh = 0; hh < 16; hh++) ld_ll2(&g_headout[hg * 16 + hh][n0], hw[hh][0], hw[hh][1]);
#pragma unroll
                    for (int hh = 0; hh < 16; hh++) ok = ok && ll_ok(hw[hh][0], tag) && ll_ok(hw[hh][1], tag);
                    if (ok || ++spins > SPIN_LIMIT) break;
                }
#pragma unroll
                for (int hh = 0; hh < 16; hh++) { a0 += ll_val(hw[hh][0]); a1 += ll_val(hw[hh][1]); }
            } else if (hg == 2) {
                u64 zw[N_MLP_CTA][2];
                for (;;) {
                    bool ok = true;
#pragma unroll
                    for (int c = 0; c < N_MLP_CTA; c++) ld_ll2(&g_mlp_part[c][n0], zw[c][0], zw[c][1]);
#pragma unroll
                    for (int c = 0; c < N_MLP_CTA; c++) ok = ok && ll_ok(zw[c][0], tag) && ll_ok(zw[c][1], tag);
                    if (ok || ++spins > SPIN_LIMIT) break;
                    __nanosleep(200);
                }
#pragma unroll
                for (int c = 0; c < N_MLP_CTA; c++) { a0 += ll_val(zw[c][0]); a1 += ll_val(zw[c][1]); }
            }
            if (hg < 3) {
                sm.red[hg][cp * 2]     = a0;
                sm.red[hg][cp * 2 + 1] = a1;
            }
            __syncthreads();
            if (tid < OCOLS) {
                const int n = mc * OCOLS + tid;
                const float a  = sm.red[0][tid] + sm.red[1][tid];
                const float t  = bf16r(__bfloat162float(x[n]) + bf16r(a));
                const float zz = bf16r(bf16r(sm.red[2][tid]) + __bfloat162float(b2[n]));
                out[n] = __float2bfloat16_rn(t + zz);
            }
            if (mc == 0 && tid == 0) *reinterpret_cast<volatile unsigned*>(&g_epoch) = epoch + 1u;
        }
        DBG_STAMP(3);
    }
}

}

extern "C" void kernel_launch(void* const* d_in, const int* in_sizes, int n_in, void* d_out, int out_size) {
    const __nv_bfloat16* x  = (const __nv_bfloat16*)d_in[0];
    const __nv_bfloat16* kc = (const __nv_bfloat16*)d_in[1];
    const __nv_bfloat16* vc = (const __nv_bfloat16*)d_in[2];
    const __nv_bfloat16* wq = (const __nv_bfloat16*)d_in[3];
    const __nv_bfloat16* wo = (const __nv_bfloat16*)d_in[4];
    const __nv_bfloat16* w1 = (const __nv_bfloat16*)d_in[6];
    const __nv_bfloat16* b1 = (const __nv_bfloat16*)d_in[7];
    const __nv_bfloat16* w2 = (const __nv_bfloat16*)d_in[8];
    const __nv_bfloat16* b2 = (const __nv_bfloat16*)d_in[9];
    __nv_bfloat16* out = (__nv_bfloat16*)d_out;

    static bool attr_set = false;
    if (!attr_set) {
        cudaFuncSetAttribute(fused_decode_kernel, cudaFuncAttributeMaxDynamicSharedMemorySize, (int)sizeof(SmemLayout));
        attr_set = true;
    }
    fused_decode_kernel<<<GRID, NTHREADS, sizeof(SmemLayout)>>>(x, kc, vc, wq, wo, w1, b1, w2, b2, out);
}
```

```cpp
#include <cuda_runtime.h>
#include <cuda_bf16.h>
#include <stdint.h>

namespace {

constexpr int D_MODEL = 640;
constexpr int NHEAD   = 32;
constexpr int DH      = 128;
constexpr int SK      = 16384;
constexpr int FF      = 1728;

#define CFG_TILE 64
#define CFG_NSTAGE 4
#define CFG_DEPTH 2

constexpr int NSPLIT        = 4;
constexpr int TILE          = CFG_TILE;
constexpr int NSTAGE        = CFG_NSTAGE;
constexpr int DEPTH         = CFG_DEPTH;
constexpr int NT_HEAD       = SK / TILE;
constexpr int TILE_BYTES    = TILE * DH * 2;
constexpr int NCONS_WARPS   = 8;
constexpr int NCONS         = NCONS_WARPS * 32;
constexpr int NR            = TILE / NCONS_WARPS / 2;
constexpr int NTHREADS      = NCONS + 32;
constexpr int N_ATTN_CTA    = NHEAD * NSPLIT;
constexpr int N_MLP_CTA     = 4;
constexpr int GRID          = N_ATTN_CTA + N_MLP_CTA;
constexpr int OCOLS         = D_MODEL / NSPLIT;
constexpr int SPIN_LIMIT    = 1 << 22;

constexpr float LOG2E = 1.4426950408889634f;

typedef unsigned long long u64;

__device__ __align__(16) u64 g_qpart[NHEAD][NSPLIT][DH];
__device__ __align__(16) u64 g_part[NHEAD][NSPLIT][DH + 2];
__device__ __align__(16) u64 g_headout[NHEAD][D_MODEL];
__device__ __align__(16) u64 g_mlp_part[N_MLP_CTA][D_MODEL];
__device__ unsigned g_ticket[NHEAD];
__device__ unsigned g_epoch;

#define DBG_STAMP(i) do { } while (0)

struct __align__(128) SmemLayout {
    uint8_t  kbuf[NSTAGE][TILE_BYTES];
    uint8_t  vbuf[NSTAGE][TILE_BYTES];
    uint64_t full_k[NSTAGE];
    uint64_t full_v[NSTAGE];
    uint64_t empty[NSTAGE];
    int      valid[NSTAGE];
    float    xn[D_MODEL];
    float    q[DH];
    float    red[16][OCOLS];
    float    ms[16];
    float    ls[16];
    float    of[DH];
    __align__(16) float red2[5][D_MODEL];
};

__device__ __forceinline__ float bf16r(float x) { return __bfloat162float(__float2bfloat16_rn(x)); }
__device__ __forceinline__ float bf_lo(uint32_t u) { return __uint_as_float(u << 16); }
__device__ __forceinline__ float bf_hi(uint32_t u) { return __uint_as_float(u & 0xffff0000u); }

__device__ __forceinline__ uint32_t smem_u32(const void* p) { return (uint32_t)__cvta_generic_to_shared(p); }
__device__ __forceinline__ void mbar_init(uint64_t* bar, uint32_t count) {
    asm volatile("mbarrier.init.shared::cta.b64 [%0], %1;" ::"r"(smem_u32(bar)), "r"(count) : "memory");
}
__device__ __forceinline__ void mbar_expect_tx(uint64_t* bar, uint32_t bytes) {
    asm volatile("mbarrier.arrive.expect_tx.shared::cta.b64 _, [%0], %1;" ::"r"(smem_u32(bar)), "r"(bytes) : "memory");
}
__device__ __forceinline__ void mbar_arrive(uint64_t* bar) {
    asm volatile("mbarrier.arrive.shared::cta.b64 _, [%0];" ::"r"(smem_u32(bar)) : "memory");
}
__device__ __forceinline__ bool mbar_try_wait(uint64_t* bar, uint32_t parity) {
    uint32_t ok;
    asm volatile(
        "{\n\t.reg .pred p;\n\t"
        "mbarrier.try_wait.parity.shared::cta.b64 p, [%1], %2;\n\t"
        "selp.u32 %0, 1, 0, p;\n\t}"
        : "=r"(ok)
        : "r"(smem_u32(bar)), "r"(parity)
        : "memory");
    return ok != 0;
}
__device__ __forceinline__ void mbar_wait(uint64_t* bar, uint32_t parity) {
    while (!mbar_try_wait(bar, parity)) {
    }
}
__device__ __forceinline__ void bulk_g2s(void* dst, const void* src, uint32_t bytes, uint64_t* bar, uint64_t policy) {
    asm volatile(
        "cp.async.bulk.shared::cluster.global.mbarrier::complete_tx::bytes.L2::cache_hint [%0], [%1], %2, [%3], %4;"
        ::"r"(smem_u32(dst)), "l"(src), "r"(bytes), "r"(smem_u32(bar)), "l"(policy)
        : "memory");
}
__device__ __forceinline__ uint4 ldg_nc(const void* p) {
    uint4 r;
    asm volatile("ld.global.nc.L1::no_allocate.v4.u32 {%0,%1,%2,%3}, [%4];"
                 : "=r"(r.x), "=r"(r.y), "=r"(r.z), "=r"(r.w)
                 : "l"(p));
    return r;
}
__device__ __forceinline__ uint4 lds128(const void* p) {
    uint4 r;
    asm volatile("ld.shared.v4.u32 {%0,%1,%2,%3}, [%4];"
                 : "=r"(r.x), "=r"(r.y), "=r"(r.z), "=r"(r.w)
                 : "r"(smem_u32(p)));
    return r;
}
__device__ __forceinline__ void named_bar_sync(int id, int n) {
    asm volatile("bar.sync %0, %1;" ::"r"(id), "r"(n) : "memory");
}
__device__ __forceinline__ void st_ll(u64* p, float v, unsigned tag) {
    const u64 w = ((u64)tag << 32) | (u64)__float_as_uint(v);
    asm volatile("st.relaxed.gpu.global.b64 [%0], %1;" ::"l"(p), "l"(w) : "memory");
}
__device__ __forceinline__ u64 ld_ll(const u64* p) {
    u64 w;
    asm volatile("ld.relaxed.gpu.global.b64 %0, [%1];" : "=l"(w) : "l"(p) : "memory");
    return w;
}
__device__ __forceinline__ void ld_ll2(const u64* p, u64& a, u64& b) {
    asm volatile("ld.relaxed.gpu.global.v2.b64 {%0,%1}, [%2];" : "=l"(a), "=l"(b) : "l"(p) : "memory");
}
__device__ __forceinline__ bool ll_ok(u64 w, unsigned tag) { return (unsigned)(w >> 32) == tag; }
__device__ __forceinline__ float ll_val(u64 w) { return __uint_as_float((unsigned)w); }

__device__ __forceinline__ void fma8(float* acc, float xv, const uint4& w) {
    acc[0] = fmaf(xv, bf_lo(w.x), acc[0]); acc[1] = fmaf(xv, bf_hi(w.x), acc[1]);
    acc[2] = fmaf(xv, bf_lo(w.y), acc[2]); acc[3] = fmaf(xv, bf_hi(w.y), acc[3]);
    acc[4] = fmaf(xv, bf_lo(w.z), acc[4]); acc[5] = fmaf(xv, bf_hi(w.z), acc[5]);
    acc[6] = fmaf(xv, bf_lo(w.w), acc[6]); acc[7] = fmaf(xv, bf_hi(w.w), acc[7]);
}

__device__ void layernorm_bf16(const float* in, float* out, float* scr, int tid, int nthr, int bar_id) {
    const int lane = tid & 31, wid = tid >> 5, nw = nthr >> 5;
    float s = 0.f;
    for (int i = tid; i < D_MODEL; i += nthr) s += in[i];
#pragma unroll
    for (int o = 16; o > 0; o >>= 1) s += __shfl_xor_sync(0xffffffffu, s, o);
    if (lane == 0) scr[wid] = s;
    named_bar_sync(bar_id, nthr);
    float tot = 0.f;
    for (int w = 0; w < nw; w++) tot += scr[w];
    const float mean = tot * (1.0f / D_MODEL);
    float vs = 0.f;
    for (int i = tid; i < D_MODEL; i += nthr) {
        float d = in[i] - mean;
        vs += d * d;
    }
#pragma unroll
    for (int o = 16; o > 0; o >>= 1) vs += __shfl_xor_sync(0xffffffffu, vs, o);
    if (lane == 0) scr[32 + wid] = vs;
    named_bar_sync(bar_id, nthr);
    float vtot = 0.f;
    for (int w = 0; w < nw; w++) vtot += scr[32 + w];
    const float m_b = bf16r(mean);
    const float v_b = bf16r(vtot * (1.0f / D_MODEL));
    const float den = bf16r(sqrtf(bf16r(v_b + 1e-5f)));
    for (int i = tid; i < D_MODEL; i += nthr) {
        float d = bf16r(in[i] - m_b);
        out[i]  = bf16r(d / den);
    }
    named_bar_sync(bar_id, nthr);
}

__device__ __forceinline__ float gelu_tanh(float x) {
    const float k0 = 0.7978845608028654f, k1 = 0.044715f;
    float inner = k0 * (x + k1 * x * x * x);
    return 0.5f * x * (1.0f + tanhf(inner));
}

__global__ void __launch_bounds__(NTHREADS, 1)
fused_decode_kernel(const __nv_bfloat16* __restrict__ x,
                    const __nv_bfloat16* __restrict__ kc,
                    const __nv_bfloat16* __restrict__ vc,
                    const __nv_bfloat16* __restrict__ wq,
                    const __nv_bfloat16* __restrict__ wo,
                    const __nv_bfloat16* __restrict__ w1,
                    const __nv_bfloat16* __restrict__ b1,
                    const __nv_bfloat16* __restrict__ w2,
                    const __nv_bfloat16* __restrict__ b2,
                    __nv_bfloat16* __restrict__ out) {
    extern __shared__ uint8_t smem_raw[];
    SmemLayout& sm = *reinterpret_cast<SmemLayout*>(smem_raw);
    const int tid  = threadIdx.x;
    const int lane = tid & 31;
    const int wid  = tid >> 5;
    const int cta  = blockIdx.x;
    DBG_STAMP(0);

    const unsigned epoch = *reinterpret_cast<volatile unsigned*>(&g_epoch);
    const unsigned tag   = epoch + 1u;

    if (cta < N_ATTN_CTA) {
        const int h     = cta % NHEAD;
        const int split = cta / NHEAD;

        const uint8_t* kbase = reinterpret_cast<const uint8_t*>(kc) + (size_t)h * SK * (DH * 2);
        const uint8_t* vbase = reinterpret_cast<const uint8_t*>(vc) + (size_t)h * SK * (DH * 2);
        const int l16q = tid & 15;
        const int rgq  = tid >> 4;
        uint4 wqr[10];
        float xr[3];
        if (wid < NCONS_WARPS) {
#pragma unroll
            for (int u = 0; u < 3; u++) {
                const int i = tid + u * NCONS;
                xr[u] = (i < D_MODEL) ? __bfloat162float(x[i]) : 0.f;
            }
            const uint8_t* wbase = reinterpret_cast<const uint8_t*>(wq) + (size_t)h * DH * 2 + l16q * 16;
#pragma unroll
            for (int u = 0; u < 10; u++)
                wqr[u] = ldg_nc(wbase + (size_t)(split * 160 + rgq + 16 * u) * (NHEAD * DH * 2));
        }
        if (tid == NCONS) {
#pragma unroll
            for (int s = 0; s < NSTAGE; s++) {
                mbar_init(&sm.full_k[s], 1);
                mbar_init(&sm.full_v[s], 1);
                mbar_init(&sm.empty[s], NCONS_WARPS);
            }
            asm volatile("fence.mbarrier_init.release.cluster;" ::: "memory");
        }
        __syncthreads();

        if (wid == NCONS_WARPS) {
            if (lane == 0) {
                uint64_t policy;
                asm volatile("createpolicy.fractional.L2::evict_first.b64 %0, 1.0;" : "=l"(policy));
#pragma unroll
                for (int s = 0; s < NSTAGE; s++) {
                    const int t = split + NSPLIT * s;
                    sm.valid[s] = 1;
                    mbar_expect_tx(&sm.full_k[s], TILE_BYTES);
                    bulk_g2s(sm.kbuf[s], kbase + (size_t)t * TILE_BYTES, TILE_BYTES, &sm.full_k[s], policy);
                    mbar_expect_tx(&sm.full_v[s], TILE_BYTES);
                    bulk_g2s(sm.vbuf[s], vbase + (size_t)t * TILE_BYTES, TILE_BYTES, &sm.full_v[s], policy);
                }
                constexpr unsigned NSTATIC = NSTAGE * NSPLIT;
                const unsigned tbase = epoch * (unsigned)(NT_HEAD - NSTATIC + NSPLIT) - NSTATIC;
                unsigned next = atomicAdd(&g_ticket[h], 1u) - tbase;
                for (int it = NSTAGE;; it++) {
                    const int s = it % NSTAGE;
                    const unsigned t = next;
                    if (t < (unsigned)NT_HEAD) next = atomicAdd(&g_ticket[h], 1u) - tbase;
                    const int d = it - DEPTH;
                    mbar_wait(&sm.empty[d % NSTAGE], (d / NSTAGE) & 1);
                    if (t >= (unsigned)NT_HEAD) {
                        sm.valid[s] = 0;
                        mbar_arrive(&sm.full_k[s]);
                        break;
                    }
                    sm.valid[s] = 1;
                    mbar_expect_tx(&sm.full_k[s], TILE_BYTES);
                    bulk_g2s(sm.kbuf[s], kbase + (size_t)t * TILE_BYTES, TILE_BYTES, &sm.full_k[s], policy);
                    mbar_expect_tx(&sm.full_v[s], TILE_BYTES);
                    bulk_g2s(sm.vbuf[s], vbase + (size_t)t * TILE_BYTES, TILE_BYTES, &sm.full_v[s], policy);
                }
            }
            return;
        }

#pragma unroll
        for (int u = 0; u < 3; u++) {
            const int i = tid + u * NCONS;
            if (i < D_MODEL) sm.xn[i] = xr[u];
        }
        named_bar_sync(1, NCONS);
        layernorm_bf16(sm.xn, sm.xn, &sm.red[0][0], tid, NCONS, 1);
        DBG_STAMP(4);

        {
            float acc[8];
#pragma unroll
            for (int j = 0; j < 8; j++) acc[j] = 0.f;
#pragma unroll
            for (int u = 0; u < 10; u++) fma8(acc, sm.xn[split * 160 + rgq + 16 * u], wqr[u]);
#pragma unroll
            for (int j = 0; j < 8; j++) sm.red[rgq][l16q * 8 + j] = acc[j];
            DBG_STAMP(5);
            named_bar_sync(1, NCONS);
            if (tid < DH) {
                float s = 0.f;
#pragma unroll
                for (int r = 0; r < 16; r++) s += sm.red[r][tid];
                st_ll(&g_qpart[h][split][tid], s, tag);
                u64 w[NSPLIT];
                int spins = 0;
                for (;;) {
                    bool ok = true;
#pragma unroll
                    for (int i = 0; i < NSPLIT; i++) w[i] = ld_ll(&g_qpart[h][i][tid]);
#pragma unroll
                    for (int i = 0; i < NSPLIT; i++) ok = ok && ll_ok(w[i], tag);
                    if (ok || ++spins > SPIN_LIMIT) break;
                }
                sm.q[tid] = bf16r((ll_val(w[0]) + ll_val(w[1])) + (ll_val(w[2]) + ll_val(w[3])));
            }
            named_bar_sync(1, NCONS);
        }
        DBG_STAMP(1);

        const int cgo = tid % 20;
        const int rgo = tid / 20;
        uint4 wor[11];
        if (rgo < 12) {
            const uint8_t* wbase = reinterpret_cast<const uint8_t*>(wo) + (size_t)h * DH * (D_MODEL * 2) + split * (OCOLS * 2) + cgo * 16;
#pragma unroll
            for (int u = 0; u < 11; u++) {
                const int row = rgo + 12 * u;
                if (u < 10 || row < DH) wor[u] = ldg_nc(wbase + (size_t)row * (D_MODEL * 2));
            }
        }

        const int half = lane >> 4;
        const int l16  = lane & 15;
        float qf[8];
#pragma unroll
        for (int j = 0; j < 8; j++) qf[j] = sm.q[l16 * 8 + j];

        float m = -INFINITY, l = 0.f;
        float o[8];
#pragma unroll
        for (int j = 0; j < 8; j++) o[j] = 0.f;
        const float scale = 0.08838834764831845f;
        const int row_off = (wid * (2 * NR) + half) * (DH * 2) + l16 * 16;

        int s = 0;
        uint32_t ph = 0;
#pragma unroll 1
        for (;;) {
            mbar_wait(&sm.full_k[s], ph);
            if (*reinterpret_cast<volatile int*>(&sm.valid[s]) == 0) break;
            uint4 kk[NR];
#pragma unroll
            for (int i = 0; i < NR; i++) kk[i] = lds128(sm.kbuf[s] + row_off + i * 2 * (DH * 2));
            float sc[NR];
#pragma unroll
            for (int i = 0; i < NR; i++) {
                float a = qf[0] * bf_lo(kk[i].x);
                a = fmaf(qf[1], bf_hi(kk[i].x), a);
                a = fmaf(qf[2], bf_lo(kk[i].y), a);
                a = fmaf(qf[3], bf_hi(kk[i].y), a);
                a = fmaf(qf[4], bf_lo(kk[i].z), a);
                a = fmaf(qf[5], bf_hi(kk[i].z), a);
                a = fmaf(qf[6], bf_lo(kk[i].w), a);
                a = fmaf(qf[7], bf_hi(kk[i].w), a);
                sc[i] = a;
            }
#pragma unroll
            for (int off = 8; off > 0; off >>= 1) {
#pragma unroll
                for (int i = 0; i < NR; i++) sc[i] += __shfl_xor_sync(0xffffffffu, sc[i], off);
            }
#pragma unroll
            for (int i = 0; i < NR; i++) sc[i] = bf16r(bf16r(sc[i]) * scale);
            float mnew = m;
#pragma unroll
            for (int i = 0; i < NR; i++) mnew = fmaxf(mnew, sc[i]);
            const float corr = exp2f((m - mnew) * LOG2E);
            float p[NR];
            float ps = 0.f;
#pragma unroll
            for (int i = 0; i < NR; i++) {
                p[i] = exp2f((sc[i] - mnew) * LOG2E);
                ps += p[i];
            }
            l = l * corr + ps;
            m = mnew;
#pragma unroll
            for (int j = 0; j < 8; j++) o[j] *= corr;

            mbar_wait(&sm.full_v[s], ph);
            uint4 vv[NR];
#pragma unroll
            for (int i = 0; i < NR; i++) vv[i] = lds128(sm.vbuf[s] + row_off + i * 2 * (DH * 2));
#pragma unroll
            for (int i = 0; i < NR; i++) fma8(o, p[i], vv[i]);
            __syncwarp();
            if (lane == 0) mbar_arrive(&sm.empty[s]);
            if (++s == NSTAGE) { s = 0; ph ^= 1; }
        }
        DBG_STAMP(2);

        {
            const int st = wid * 2 + half;
#pragma unroll
            for (int j = 0; j < 8; j++) sm.red[st][l16 * 8 + j] = o[j];
            if (l16 == 0) {
                sm.ms[st] = m;
                sm.ls[st] = l;
            }
            named_bar_sync(1, NCONS);
            if (tid < DH) {
                float M = sm.ms[0];
#pragma unroll
                for (int i = 1; i < 16; i++) M = fmaxf(M, sm.ms[i]);
                float L = 0.f, O = 0.f;
                if (M > -INFINITY) {
#pragma unroll
                    for (int i = 0; i < 16; i++) {
                        const float w = exp2f((sm.ms[i] - M) * LOG2E);
                        L += w * sm.ls[i];
                        O += w * sm.red[i][tid];
                    }
                }
                st_ll(&g_part[h][split][tid], O, tag);
                if (tid == 0) {
                    st_ll(&g_part[h][split][DH], M, tag);
                    st_ll(&g_part[h][split][DH + 1], L, tag);
                }
                u64 wo_[NSPLIT], wm[NSPLIT], wl[NSPLIT];
                int spins = 0;
                for (;;) {
                    bool ok = true;
#pragma unroll
                    for (int i = 0; i < NSPLIT; i++) {
                        wo_[i] = ld_ll(&g_part[h][i][tid]);
                        ld_ll2(&g_part[h][i][DH], wm[i], wl[i]);
                    }
#pragma unroll
                    for (int i = 0; i < NSPLIT; i++) ok = ok && ll_ok(wo_[i], tag) && ll_ok(wm[i], tag) && ll_ok(wl[i], tag);
                    if (ok || ++spins > SPIN_LIMIT) break;
                }
                float MM = -INFINITY;
#pragma unroll
                for (int i = 0; i < NSPLIT; i++) MM = fmaxf(MM, ll_val(wm[i]));
                float LL = 0.f, OO = 0.f;
#pragma unroll
                for (int i = 0; i < NSPLIT; i++) {
                    const float mi = ll_val(wm[i]);
                    const float w  = (mi > -INFINITY) ? exp2f((mi - MM) * LOG2E) : 0.f;
                    LL += w * ll_val(wl[i]);
                    OO += w * ll_val(wo_[i]);
                }
                sm.of[tid] = bf16r(OO / LL);
            }
            named_bar_sync(1, NCONS);
        }
        DBG_STAMP(7);

        {
            if (rgo < 12) {
                float acc[8];
#pragma unroll
                for (int j = 0; j < 8; j++) acc[j] = 0.f;
#pragma unroll
                for (int u = 0; u < 11; u++) {
                    const int row = rgo + 12 * u;
                    if (u < 10 || row < DH) fma8(acc, sm.of[row], wor[u]);
                }
#pragma unroll
                for (int j = 0; j < 8; j++) sm.red[rgo][cgo * 8 + j] = acc[j];
            }
            named_bar_sync(1, NCONS);
            if (tid < OCOLS) {
                float a = 0.f;
#pragma unroll
                for (int r = 0; r < 12; r++) a += sm.red[r][tid];
                st_ll(&g_headout[h][split * OCOLS + tid], a, tag);
            }
        }
        DBG_STAMP(3);
        return;
    }

    {
        const int mc = cta - N_ATTN_CTA;
        for (int i = tid; i < D_MODEL; i += NTHREADS) sm.xn[i] = __bfloat162float(x[i]);
        named_bar_sync(1, NTHREADS);
        layernorm_bf16(sm.xn, sm.xn, &sm.red[0][0], tid, NTHREADS, 1);
        layernorm_bf16(sm.xn, sm.xn, &sm.red[0][0], tid, NTHREADS, 1);

        constexpr int CPC = FF / N_MLP_CTA;
        float* hs = reinterpret_cast<float*>(sm.vbuf);
        {
            constexpr int NCG = CPC / 8;
            constexpr int NRG = 5;
            const int cg = tid % NCG, rg = tid / NCG;
            if (rg < NRG) {
                float acc[8];
#pragma unroll
                for (int j = 0; j < 8; j++) acc[j] = 0.f;
                const uint8_t* wbase = reinterpret_cast<const uint8_t*>(w1) + (size_t)(mc * CPC + cg * 8) * 2;
#pragma unroll 1
                for (int it = 0; it < 8; it++) {
                    uint4 w[16];
#pragma unroll
                    for (int u = 0; u < 16; u++) w[u] = ldg_nc(wbase + (size_t)(rg * 128 + it * 16 + u) * (FF * 2));
#pragma unroll
                    for (int u = 0; u < 16; u++) fma8(acc, sm.xn[rg * 128 + it * 16 + u], w[u]);
                }
#pragma unroll
                for (int j = 0; j < 8; j++) sm.red2[rg][cg * 8 + j] = acc[j];
            }
            __syncthreads();
            for (int c = tid; c < CPC; c += NTHREADS) {
                float s = 0.f;
#pragma unroll
                for (int r = 0; r < NRG; r++) s += sm.red2[r][c];
                const int f = mc * CPC + c;
                float u = bf16r(bf16r(s) + __bfloat162float(b1[f]));
                hs[c] = bf16r(gelu_tanh(u));
            }
            __syncthreads();
        }
        DBG_STAMP(1);
        {
            const int cg = tid % 80, rgp = tid / 80;
            if (rgp < 3) {
                float acc[8];
#pragma unroll
                for (int j = 0; j < 8; j++) acc[j] = 0.f;
                const uint8_t* wbase = reinterpret_cast<const uint8_t*>(w2) + (size_t)(mc * CPC) * (D_MODEL * 2) + cg * 16;
#pragma unroll 1
                for (int it = 0; it < 9; it++) {
                    uint4 w[16];
#pragma unroll
                    for (int u = 0; u < 16; u++) w[u] = ldg_nc(wbase + (size_t)(rgp * 144 + it * 16 + u) * (D_MODEL * 2));
#pragma unroll
                    for (int u = 0; u < 16; u++) fma8(acc, hs[rgp * 144 + it * 16 + u], w[u]);
                }
#pragma unroll
                for (int j = 0; j < 8; j++) sm.red2[rgp][cg * 8 + j] = acc[j];
            }
            __syncthreads();
            for (int n = tid; n < D_MODEL; n += NTHREADS)
                st_ll(&g_mlp_part[mc][n], sm.red2[0][n] + sm.red2[1][n] + sm.red2[2][n], tag);
        }
        DBG_STAMP(2);

        {
            const int cp = tid % 80, hg = tid / 80;
            const int n0 = mc * OCOLS + cp * 2;
            float a0 = 0.f, a1 = 0.f;
            int spins = 0;
            if (hg < 2) {
                while (!ll_ok(ld_ll(&g_headout[hg * 16][n0]), tag) && ++spins < SPIN_LIMIT) __nanosleep(100);
                u64 hw[16][2];
                for (;;) {
                    bool ok = true;
#pragma unroll
                    for (int hh = 0; hh < 16; hh++) ld_ll2(&g_headout[hg * 16 + hh][n0], hw[hh][0], hw[hh][1]);
#pragma unroll
                    for (int hh = 0; hh < 16; hh++) ok = ok && ll_ok(hw[hh][0], tag) && ll_ok(hw[hh][1], tag);
                    if (ok || ++spins > SPIN_LIMIT) break;
                }
#pragma unroll
                for (int hh = 0; hh < 16; hh++) { a0 += ll_val(hw[hh][0]); a1 += ll_val(hw[hh][1]); }
            } else if (hg == 2) {
                u64 zw[N_MLP_CTA][2];
                for (;;) {
                    bool ok = true;
#pragma unroll
                    for (int c = 0; c < N_MLP_CTA; c++) ld_ll2(&g_mlp_part[c][n0], zw[c][0], zw[c][1]);
#pragma unroll
                    for (int c = 0; c < N_MLP_CTA; c++) ok = ok && ll_ok(zw[c][0], tag) && ll_ok(zw[c][1], tag);
                    if (ok || ++spins > SPIN_LIMIT) break;
                    __nanosleep(200);
                }
#pragma unroll
                for (int c = 0; c < N_MLP_CTA; c++) { a0 += ll_val(zw[c][0]); a1 += ll_val(zw[c][1]); }
            }
            if (hg < 3) {
                sm.red[hg][cp * 2]     = a0;
                sm.red[hg][cp * 2 + 1] = a1;
            }
            __syncthreads();
            if (tid < OCOLS) {
                const int n = mc * OCOLS + tid;
                const float a  = sm.red[0][tid] + sm.red[1][tid];
                const float t  = bf16r(__bfloat162float(x[n]) + bf16r(a));
                const float zz = bf16r(bf16r(sm.red[2][tid]) + __bfloat162float(b2[n]));
                out[n] = __float2bfloat16_rn(t + zz);
            }
            if (mc == 0 && tid == 0) *reinterpret_cast<volatile unsigned*>(&g_epoch) = epoch + 1u;
        }
        DBG_STAMP(3);
    }
}

}

extern "C" void kernel_launch(void* const* d_in, const int* in_sizes, int n_in, void* d_out, int out_size) {
    const __nv_bfloat16* x  = (const __nv_bfloat16*)d_in[0];
    const __nv_bfloat16* kc = (const __nv_bfloat16*)d_in[1];
    const __nv_bfloat16* vc = (const __nv_bfloat16*)d_in[2];
    const __nv_bfloat16* wq = (const __nv_bfloat16*)d_in[3];
    const __nv_bfloat16* wo = (const __nv_bfloat16*)d_in[4];
    const __nv_bfloat16* w1 = (const __nv_bfloat16*)d_in[6];
    const __nv_bfloat16* b1 = (const __nv_bfloat16*)d_in[7];
    const __nv_bfloat16* w2 = (const __nv_bfloat16*)d_in[8];
    const __nv_bfloat16* b2 = (const __nv_bfloat16*)d_in[9];
    __nv_bfloat16* out = (__nv_bfloat16*)d_out;

    static bool attr_set = false;
    if (!attr_set) {
        cudaFuncSetAttribute(fused_decode_kernel, cudaFuncAttributeMaxDynamicSharedMemorySize, (int)sizeof(SmemLayout));
        attr_set = true;
    }
    fused_decode_kernel<<<GRID, NTHREADS, sizeof(SmemLayout)>>>(x, kc, vc, wq, wo, w1, b1, w2, b2, out);
}
```

```cpp
#include <cuda_runtime.h>
#include <cuda_bf16.h>
#include <stdint.h>

namespace {

constexpr int D_MODEL = 640;
constexpr int NHEAD   = 32;
constexpr int DH      = 128;
constexpr int SK      = 16384;
constexpr int FF      = 1728;

#define CFG_TILE 32
#define CFG_NSTAGE 10
#define CFG_DEPTH 4

constexpr int NSPLIT        = 4;
constexpr int TILE          = CFG_TILE;
constexpr int NSTAGE        = CFG_NSTAGE;
constexpr int DEPTH         = CFG_DEPTH;
constexpr int NT_HEAD       = SK / TILE;
constexpr int TILE_BYTES    = TILE * DH * 2;
constexpr int NCONS_WARPS   = 8;
constexpr int NCONS         = NCONS_WARPS * 32;
constexpr int NR            = TILE / NCONS_WARPS / 2;
constexpr int NTHREADS      = NCONS + 32;
constexpr int N_ATTN_CTA    = NHEAD * NSPLIT;
constexpr int N_MLP_CTA     = 4;
constexpr int GRID          = N_ATTN_CTA + N_MLP_CTA;
constexpr int OCOLS         = D_MODEL / NSPLIT;
constexpr int SPIN_LIMIT    = 1 << 22;

constexpr float LOG2E = 1.4426950408889634f;

typedef unsigned long long u64;

__device__ __align__(16) u64 g_qpart[NHEAD][NSPLIT][DH];
__device__ __align__(16) u64 g_part[NHEAD][NSPLIT][DH + 2];
__device__ __align__(16) u64 g_headout[NHEAD][D_MODEL];
__device__ __align__(16) u64 g_mlp_part[N_MLP_CTA][D_MODEL];
__device__ unsigned g_ticket[NHEAD];
__device__ unsigned g_epoch;

#define DBG_STAMP(i) do { } while (0)

struct __align__(128) SmemLayout {
    uint8_t  kbuf[NSTAGE][TILE_BYTES];
    uint8_t  vbuf[NSTAGE][TILE_BYTES];
    uint64_t full_k[NSTAGE];
    uint64_t full_v[NSTAGE];
    uint64_t empty[NSTAGE];
    int      valid[NSTAGE];
    float    xn[D_MODEL];
    float    q[DH];
    float    red[16][OCOLS];
    float    ms[16];
    float    ls[16];
    float    of[DH];
    __align__(16) float red2[5][D_MODEL];
};

__device__ __forceinline__ float bf16r(float x) { return __bfloat162float(__float2bfloat16_rn(x)); }
__device__ __forceinline__ float bf_lo(uint32_t u) { return __uint_as_float(u << 16); }
__device__ __forceinline__ float bf_hi(uint32_t u) { return __uint_as_float(u & 0xffff0000u); }

__device__ __forceinline__ uint32_t smem_u32(const void* p) { return (uint32_t)__cvta_generic_to_shared(p); }
__device__ __forceinline__ void mbar_init(uint64_t* bar, uint32_t count) {
    asm volatile("mbarrier.init.shared::cta.b64 [%0], %1;" ::"r"(smem_u32(bar)), "r"(count) : "memory");
}
__device__ __forceinline__ void mbar_expect_tx(uint64_t* bar, uint32_t bytes) {
    asm volatile("mbarrier.arrive.expect_tx.shared::cta.b64 _, [%0], %1;" ::"r"(smem_u32(bar)), "r"(bytes) : "memory");
}
__device__ __forceinline__ void mbar_arrive(uint64_t* bar) {
    asm volatile("mbarrier.arrive.shared::cta.b64 _, [%0];" ::"r"(smem_u32(bar)) : "memory");
}
__device__ __forceinline__ bool mbar_try_wait(uint64_t* bar, uint32_t parity) {
    uint32_t ok;
    asm volatile(
        "{\n\t.reg .pred p;\n\t"
        "mbarrier.try_wait.parity.shared::cta.b64 p, [%1], %2;\n\t"
        "selp.u32 %0, 1, 0, p;\n\t}"
        : "=r"(ok)
        : "r"(smem_u32(bar)), "r"(parity)
        : "memory");
    return ok != 0;
}
__device__ __forceinline__ void mbar_wait(uint64_t* bar, uint32_t parity) {
    while (!mbar_try_wait(bar, parity)) {
    }
}
__device__ __forceinline__ void bulk_g2s(void* dst, const void* src, uint32_t bytes, uint64_t* bar, uint64_t policy) {
    asm volatile(
        "cp.async.bulk.shared::cluster.global.mbarrier::complete_tx::bytes.L2::cache_hint [%0], [%1], %2, [%3], %4;"
        ::"r"(smem_u32(dst)), "l"(src), "r"(bytes), "r"(smem_u32(bar)), "l"(policy)
        : "memory");
}
__device__ __forceinline__ uint4 ldg_nc(const void* p) {
    uint4 r;
    asm volatile("ld.global.nc.L1::no_allocate.v4.u32 {%0,%1,%2,%3}, [%4];"
                 : "=r"(r.x), "=r"(r.y), "=r"(r.z), "=r"(r.w)
                 : "l"(p));
    return r;
}
__device__ __forceinline__ uint4 lds128(const void* p) {
    uint4 r;
    asm volatile("ld.shared.v4.u32 {%0,%1,%2,%3}, [%4];"
                 : "=r"(r.x), "=r"(r.y), "=r"(r.z), "=r"(r.w)
                 : "r"(smem_u32(p)));
    return r;
}
__device__ __forceinline__ void named_bar_sync(int id, int n) {
    asm volatile("bar.sync %0, %1;" ::"r"(id), "r"(n) : "memory");
}
__device__ __forceinline__ void st_ll(u64* p, float v, unsigned tag) {
    const u64 w = ((u64)tag << 32) | (u64)__float_as_uint(v);
    asm volatile("st.relaxed.gpu.global.b64 [%0], %1;" ::"l"(p), "l"(w) : "memory");
}
__device__ __forceinline__ u64 ld_ll(const u64* p) {
    u64 w;
    asm volatile("ld.relaxed.gpu.global.b64 %0, [%1];" : "=l"(w) : "l"(p) : "memory");
    return w;
}
__device__ __forceinline__ void ld_ll2(const u64* p, u64& a, u64& b) {
    asm volatile("ld.relaxed.gpu.global.v2.b64 {%0,%1}, [%2];" : "=l"(a), "=l"(b) : "l"(p) : "memory");
}
__device__ __forceinline__ bool ll_ok(u64 w, unsigned tag) { return (unsigned)(w >> 32) == tag; }
__device__ __forceinline__ float ll_val(u64 w) { return __uint_as_float((unsigned)w); }

__device__ __forceinline__ void fma8(float* acc, float xv, const uint4& w) {
    acc[0] = fmaf(xv, bf_lo(w.x), acc[0]); acc[1] = fmaf(xv, bf_hi(w.x), acc[1]);
    acc[2] = fmaf(xv, bf_lo(w.y), acc[2]); acc[3] = fmaf(xv, bf_hi(w.y), acc[3]);
    acc[4] = fmaf(xv, bf_lo(w.z), acc[4]); acc[5] = fmaf(xv, bf_hi(w.z), acc[5]);
    acc[6] = fmaf(xv, bf_lo(w.w), acc[6]); acc[7] = fmaf(xv, bf_hi(w.w), acc[7]);
}

__device__ void layernorm_bf16(const float* in, float* out, float* scr, int tid, int nthr, int bar_id) {
    const int lane = tid & 31, wid = tid >> 5, nw = nthr >> 5;
    float s = 0.f;
    for (int i = tid; i < D_MODEL; i += nthr) s += in[i];
#pragma unroll
    for (int o = 16; o > 0; o >>= 1) s += __shfl_xor_sync(0xffffffffu, s, o);
    if (lane == 0) scr[wid] = s;
    named_bar_sync(bar_id, nthr);
    float tot = 0.f;
    for (int w = 0; w < nw; w++) tot += scr[w];
    const float mean = tot * (1.0f / D_MODEL);
    float vs = 0.f;
    for (int i = tid; i < D_MODEL; i += nthr) {
        float d = in[i] - mean;
        vs += d * d;
    }
#pragma unroll
    for (int o = 16; o > 0; o >>= 1) vs += __shfl_xor_sync(0xffffffffu, vs, o);
    if (lane == 0) scr[32 + wid] = vs;
    named_bar_sync(bar_id, nthr);
    float vtot = 0.f;
    for (int w = 0; w < nw; w++) vtot += scr[32 + w];
    const float m_b = bf16r(mean);
    const float v_b = bf16r(vtot * (1.0f / D_MODEL));
    const float den = bf16r(sqrtf(bf16r(v_b + 1e-5f)));
    for (int i = tid; i < D_MODEL; i += nthr) {
        float d = bf16r(in[i] - m_b);
        out[i]  = bf16r(d / den);
    }
    named_bar_sync(bar_id, nthr);
}

__device__ __forceinline__ float gelu_tanh(float x) {
    const float k0 = 0.7978845608028654f, k1 = 0.044715f;
    float inner = k0 * (x + k1 * x * x * x);
    return 0.5f * x * (1.0f + tanhf(inner));
}

__global__ void __launch_bounds__(NTHREADS, 1)
fused_decode_kernel(const __nv_bfloat16* __restrict__ x,
                    const __nv_bfloat16* __restrict__ kc,
                    const __nv_bfloat16* __restrict__ vc,
                    const __nv_bfloat16* __restrict__ wq,
                    const __nv_bfloat16* __restrict__ wo,
                    const __nv_bfloat16* __restrict__ w1,
                    const __nv_bfloat16* __restrict__ b1,
                    const __nv_bfloat16* __restrict__ w2,
                    const __nv_bfloat16* __restrict__ b2,
                    __nv_bfloat16* __restrict__ out) {
    extern __shared__ uint8_t smem_raw[];
    SmemLayout& sm = *reinterpret_cast<SmemLayout*>(smem_raw);
    const int tid  = threadIdx.x;
    const int lane = tid & 31;
    const int wid  = tid >> 5;
    const int cta  = blockIdx.x;
    DBG_STAMP(0);

    const unsigned epoch = *reinterpret_cast<volatile unsigned*>(&g_epoch);
    const unsigned tag   = epoch + 1u;

    if (cta < N_ATTN_CTA) {
        const int h     = cta % NHEAD;
        const int split = cta / NHEAD;

        const uint8_t* kbase = reinterpret_cast<const uint8_t*>(kc) + (size_t)h * SK * (DH * 2);
        const uint8_t* vbase = reinterpret_cast<const uint8_t*>(vc) + (size_t)h * SK * (DH * 2);
        const int l16q = tid & 15;
        const int rgq  = tid >> 4;
        uint4 wqr[10];
        float xr[3];
        if (wid < NCONS_WARPS) {
#pragma unroll
            for (int u = 0; u < 3; u++) {
                const int i = tid + u * NCONS;
                xr[u] = (i < D_MODEL) ? __bfloat162float(x[i]) : 0.f;
            }
            const uint8_t* wbase = reinterpret_cast<const uint8_t*>(wq) + (size_t)h * DH * 2 + l16q * 16;
#pragma unroll
            for (int u = 0; u < 10; u++)
                wqr[u] = ldg_nc(wbase + (size_t)(split * 160 + rgq + 16 * u) * (NHEAD * DH * 2));
        }
        if (tid == NCONS) {
#pragma unroll
            for (int s = 0; s < NSTAGE; s++) {
                mbar_init(&sm.full_k[s], 1);
                mbar_init(&sm.full_v[s], 1);
                mbar_init(&sm.empty[s], NCONS_WARPS);
            }
            asm volatile("fence.mbarrier_init.release.cluster;" ::: "memory");
        }
        __syncthreads();

        if (wid == NCONS_WARPS) {
            if (lane == 0) {
                uint64_t policy;
                asm volatile("createpolicy.fractional.L2::evict_first.b64 %0, 1.0;" : "=l"(policy));
                constexpr unsigned NSTATIC = NSTAGE * NSPLIT;
                const unsigned tbase = epoch * (unsigned)(NT_HEAD - NSTATIC + NSPLIT) - NSTATIC;
                unsigned next = 0;
                for (int it = 0;; it++) {
                    const int s = it % NSTAGE;
                    unsigned t;
                    if (it < NSTAGE) {
                        t = split + NSPLIT * it;
                        if (it == NSTAGE - 1) next = atomicAdd(&g_ticket[h], 1u) - tbase;
                    } else {
                        t = next;
                        if (t < (unsigned)NT_HEAD) next = atomicAdd(&g_ticket[h], 1u) - tbase;
                        mbar_wait(&sm.empty[s], ((it / NSTAGE) - 1) & 1);
                    }
                    if (t >= (unsigned)NT_HEAD) {
                        sm.valid[s] = 0;
                        mbar_arrive(&sm.full_k[s]);
                        break;
                    }
                    if (it >= DEPTH) {
                        const int d = it - DEPTH;
                        mbar_wait(&sm.full_v[d % NSTAGE], (d / NSTAGE) & 1);
                    }
                    sm.valid[s] = 1;
                    mbar_expect_tx(&sm.full_k[s], TILE_BYTES);
                    bulk_g2s(sm.kbuf[s], kbase + (size_t)t * TILE_BYTES, TILE_BYTES, &sm.full_k[s], policy);
                    mbar_expect_tx(&sm.full_v[s], TILE_BYTES);
                    bulk_g2s(sm.vbuf[s], vbase + (size_t)t * TILE_BYTES, TILE_BYTES, &sm.full_v[s], policy);
                }
            }
            return;
        }

#pragma unroll
        for (int u = 0; u < 3; u++) {
            const int i = tid + u * NCONS;
            if (i < D_MODEL) sm.xn[i] = xr[u];
        }
        named_bar_sync(1, NCONS);
        layernorm_bf16(sm.xn, sm.xn, &sm.red[0][0], tid, NCONS, 1);
        DBG_STAMP(4);

        {
            float acc[8];
#pragma unroll
            for (int j = 0; j < 8; j++) acc[j] = 0.f;
#pragma unroll
            for (int u = 0; u < 10; u++) fma8(acc, sm.xn[split * 160 + rgq + 16 * u], wqr[u]);
#pragma unroll
            for (int j = 0; j < 8; j++) sm.red[rgq][l16q * 8 + j] = acc[j];
            DBG_STAMP(5);
            named_bar_sync(1, NCONS);
            if (tid < DH) {
                float s = 0.f;
#pragma unroll
                for (int r = 0; r < 16; r++) s += sm.red[r][tid];
                st_ll(&g_qpart[h][split][tid], s, tag);
                u64 w[NSPLIT];
                int spins = 0;
                for (;;) {
                    bool ok = true;
#pragma unroll
                    for (int i = 0; i < NSPLIT; i++) w[i] = ld_ll(&g_qpart[h][i][tid]);
#pragma unroll
                    for (int i = 0; i < NSPLIT; i++) ok = ok && ll_ok(w[i], tag);
                    if (ok || ++spins > SPIN_LIMIT) break;
                }
                sm.q[tid] = bf16r((ll_val(w[0]) + ll_val(w[1])) + (ll_val(w[2]) + ll_val(w[3])));
            }
            named_bar_sync(1, NCONS);
        }
        DBG_STAMP(1);

        const int half = lane >> 4;
        const int l16  = lane & 15;
        float qf[8];
#pragma unroll
        for (int j = 0; j < 8; j++) qf[j] = sm.q[l16 * 8 + j];

        float m = -INFINITY, l = 0.f;
        float o[8];
#pragma unroll
        for (int j = 0; j < 8; j++) o[j] = 0.f;
        const float scale = 0.08838834764831845f;
        const int row_off = (wid * (2 * NR) + half) * (DH * 2) + l16 * 16;

        int s = 0;
        uint32_t ph = 0;
#pragma unroll 1
        for (;;) {
            mbar_wait(&sm.full_k[s], ph);
            if (*reinterpret_cast<volatile int*>(&sm.valid[s]) == 0) break;
            uint4 kk[NR];
#pragma unroll
            for (int i = 0; i < NR; i++) kk[i] = lds128(sm.kbuf[s] + row_off + i * 2 * (DH * 2));
            float sc[NR];
#pragma unroll
            for (int i = 0; i < NR; i++) {
                float a = qf[0] * bf_lo(kk[i].x);
                a = fmaf(qf[1], bf_hi(kk[i].x), a);
                a = fmaf(qf[2], bf_lo(kk[i].y), a);
                a = fmaf(qf[3], bf_hi(kk[i].y), a);
                a = fmaf(qf[4], bf_lo(kk[i].z), a);
                a = fmaf(qf[5], bf_hi(kk[i].z), a);
                a = fmaf(qf[6], bf_lo(kk[i].w), a);
                a = fmaf(qf[7], bf_hi(kk[i].w), a);
                sc[i] = a;
            }
#pragma unroll
            for (int off = 8; off > 0; off >>= 1) {
#pragma unroll
                for (int i = 0; i < NR; i++) sc[i] += __shfl_xor_sync(0xffffffffu, sc[i], off);
            }
#pragma unroll
            for (int i = 0; i < NR; i++) sc[i] = bf16r(bf16r(sc[i]) * scale);
            float mnew = m;
#pragma unroll
            for (int i = 0; i < NR; i++) mnew = fmaxf(mnew, sc[i]);
            const float corr = exp2f((m - mnew) * LOG2E);
            float p[NR];
            float ps = 0.f;
#pragma unroll
            for (int i = 0; i < NR; i++) {
                p[i] = exp2f((sc[i] - mnew) * LOG2E);
                ps += p[i];
            }
            l = l * corr + ps;
            m = mnew;
#pragma unroll
            for (int j = 0; j < 8; j++) o[j] *= corr;

            mbar_wait(&sm.full_v[s], ph);
            uint4 vv[NR];
#pragma unroll
            for (int i = 0; i < NR; i++) vv[i] = lds128(sm.vbuf[s] + row_off + i * 2 * (DH * 2));
#pragma unroll
            for (int i = 0; i < NR; i++) fma8(o, p[i], vv[i]);
            __syncwarp();
            if (lane == 0) mbar_arrive(&sm.empty[s]);
            if (++s == NSTAGE) { s = 0; ph ^= 1; }
        }
        DBG_STAMP(2);

        const int cgo = tid % 20;
        const int rgo = tid / 20;
        uint4 wor[11];
        if (rgo < 12) {
            const uint8_t* wbase = reinterpret_cast<const uint8_t*>(wo) + (size_t)h * DH * (D_MODEL * 2) + split * (OCOLS * 2) + cgo * 16;
#pragma unroll
            for (int u = 0; u < 11; u++) {
                const int row = rgo + 12 * u;
                if (u < 10 || row < DH) wor[u] = ldg_nc(wbase + (size_t)row * (D_MODEL * 2));
            }
        }

        {
            const int st = wid * 2 + half;
#pragma unroll
            for (int j = 0; j < 8; j++) sm.red[st][l16 * 8 + j] = o[j];
            if (l16 == 0) {
                sm.ms[st] = m;
                sm.ls[st] = l;
            }
            named_bar_sync(1, NCONS);
            if (tid < DH) {
                float M = sm.ms[0];
#pragma unroll
                for (int i = 1; i < 16; i++) M = fmaxf(M, sm.ms[i]);
                float L = 0.f, O = 0.f;
                if (M > -INFINITY) {
#pragma unroll
                    for (int i = 0; i < 16; i++) {
                        const float w = exp2f((sm.ms[i] - M) * LOG2E);
                        L += w * sm.ls[i];
                        O += w * sm.red[i][tid];
                    }
                }
                st_ll(&g_part[h][split][tid], O, tag);
                if (tid == 0) {
                    st_ll(&g_part[h][split][DH], M, tag);
                    st_ll(&g_part[h][split][DH + 1], L, tag);
                }
                u64 wo_[NSPLIT], wm[NSPLIT], wl[NSPLIT];
                int spins = 0;
                for (;;) {
                    bool ok = true;
#pragma unroll
                    for (int i = 0; i < NSPLIT; i++) {
                        wo_[i] = ld_ll(&g_part[h][i][tid]);
                        ld_ll2(&g_part[h][i][DH], wm[i], wl[i]);
                    }
#pragma unroll
                    for (int i = 0; i < NSPLIT; i++) ok = ok && ll_ok(wo_[i], tag) && ll_ok(wm[i], tag) && ll_ok(wl[i], tag);
                    if (ok || ++spins > SPIN_LIMIT) break;
                }
                float MM = -INFINITY;
#pragma unroll
                for (int i = 0; i < NSPLIT; i++) MM = fmaxf(MM, ll_val(wm[i]));
                float LL = 0.f, OO = 0.f;
#pragma unroll
                for (int i = 0; i < NSPLIT; i++) {
                    const float mi = ll_val(wm[i]);
                    const float w  = (mi > -INFINITY) ? exp2f((mi - MM) * LOG2E) : 0.f;
                    LL += w * ll_val(wl[i]);
                    OO += w * ll_val(wo_[i]);
                }
                sm.of[tid] = bf16r(OO / LL);
            }
            named_bar_sync(1, NCONS);
        }
        DBG_STAMP(7);

        {
            if (rgo < 12) {
                float acc[8];
#pragma unroll
                for (int j = 0; j < 8; j++) acc[j] = 0.f;
#pragma unroll
                for (int u = 0; u < 11; u++) {
                    const int row = rgo + 12 * u;
                    if (u < 10 || row < DH) fma8(acc, sm.of[row], wor[u]);
                }
#pragma unroll
                for (int j = 0; j < 8; j++) sm.red[rgo][cgo * 8 + j] = acc[j];
            }
            named_bar_sync(1, NCONS);
            if (tid < OCOLS) {
                float a = 0.f;
#pragma unroll
                for (int r = 0; r < 12; r++) a += sm.red[r][tid];
                st_ll(&g_headout[h][split * OCOLS + tid], a, tag);
            }
        }
        DBG_STAMP(3);
        return;
    }

    {
        const int mc = cta - N_ATTN_CTA;
        for (int i = tid; i < D_MODEL; i += NTHREADS) sm.xn[i] = __bfloat162float(x[i]);
        named_bar_sync(1, NTHREADS);
        layernorm_bf16(sm.xn, sm.xn, &sm.red[0][0], tid, NTHREADS, 1);
        layernorm_bf16(sm.xn, sm.xn, &sm.red[0][0], tid, NTHREADS, 1);

        constexpr int CPC = FF / N_MLP_CTA;
        float* hs = reinterpret_cast<float*>(sm.vbuf);
        {
            constexpr int NCG = CPC / 8;
            constexpr int NRG = 5;
            const int cg = tid % NCG, rg = tid / NCG;
            if (rg < NRG) {
                float acc[8];
#pragma unroll
                for (int j = 0; j < 8; j++) acc[j] = 0.f;
                const uint8_t* wbase = reinterpret_cast<const uint8_t*>(w1) + (size_t)(mc * CPC + cg * 8) * 2;
#pragma unroll 1
                for (int it = 0; it < 8; it++) {
                    uint4 w[16];
#pragma unroll
                    for (int u = 0; u < 16; u++) w[u] = ldg_nc(wbase + (size_t)(rg * 128 + it * 16 + u) * (FF * 2));
#pragma unroll
                    for (int u = 0; u < 16; u++) fma8(acc, sm.xn[rg * 128 + it * 16 + u], w[u]);
                }
#pragma unroll
                for (int j = 0; j < 8; j++) sm.red2[rg][cg * 8 + j] = acc[j];
            }
            __syncthreads();
            for (int c = tid; c < CPC; c += NTHREADS) {
                float s = 0.f;
#pragma unroll
                for (int r = 0; r < NRG; r++) s += sm.red2[r][c];
                const int f = mc * CPC + c;
                float u = bf16r(bf16r(s) + __bfloat162float(b1[f]));
                hs[c] = bf16r(gelu_tanh(u));
            }
            __syncthreads();
        }
        DBG_STAMP(1);
        {
            const int cg = tid % 80, rgp = tid / 80;
            if (rgp < 3) {
                float acc[8];
#pragma unroll
                for (int j = 0; j < 8; j++) acc[j] = 0.f;
                const uint8_t* wbase = reinterpret_cast<const uint8_t*>(w2) + (size_t)(mc * CPC) * (D_MODEL * 2) + cg * 16;
#pragma unroll 1
                for (int it = 0; it < 9; it++) {
                    uint4 w[16];
#pragma unroll
                    for (int u = 0; u < 16; u++) w[u] = ldg_nc(wbase + (size_t)(rgp * 144 + it * 16 + u) * (D_MODEL * 2));
#pragma unroll
                    for (int u = 0; u < 16; u++) fma8(acc, hs[rgp * 144 + it * 16 + u], w[u]);
                }
#pragma unroll
                for (int j = 0; j < 8; j++) sm.red2[rgp][cg * 8 + j] = acc[j];
            }
            __syncthreads();
            for (int n = tid; n < D_MODEL; n += NTHREADS)
                st_ll(&g_mlp_part[mc][n], sm.red2[0][n] + sm.red2[1][n] + sm.red2[2][n], tag);
        }
        DBG_STAMP(2);

        {
            const int cp = tid % 80, hg = tid / 80;
            const int n0 = mc * OCOLS + cp * 2;
            float a0 = 0.f, a1 = 0.f;
            int spins = 0;
            if (hg < 2) {
                while (!ll_ok(ld_ll(&g_headout[hg * 16][n0]), tag) && ++spins < SPIN_LIMIT) __nanosleep(100);
                u64 hw[16][2];
                for (;;) {
                    bool ok = true;
#pragma unroll
                    for (int hh = 0; hh < 16; hh++) ld_ll2(&g_headout[hg * 16 + hh][n0], hw[hh][0], hw[hh][1]);
#pragma unroll
                    for (int hh = 0; hh < 16; hh++) ok = ok && ll_ok(hw[hh][0], tag) && ll_ok(hw[hh][1], tag);
                    if (ok || ++spins > SPIN_LIMIT) break;
                }
#pragma unroll
                for (int hh = 0; hh < 16; hh++) { a0 += ll_val(hw[hh][0]); a1 += ll_val(hw[hh][1]); }
            } else if (hg == 2) {
                u64 zw[N_MLP_CTA][2];
                for (;;) {
                    bool ok = true;
#pragma unroll
                    for (int c = 0; c < N_MLP_CTA; c++) ld_ll2(&g_mlp_part[c][n0], zw[c][0], zw[c][1]);
#pragma unroll
                    for (int c = 0; c < N_MLP_CTA; c++) ok = ok && ll_ok(zw[c][0], tag) && ll_ok(zw[c][1], tag);
                    if (ok || ++spins > SPIN_LIMIT) break;
                    __nanosleep(200);
                }
#pragma unroll
                for (int c = 0; c < N_MLP_CTA; c++) { a0 += ll_val(zw[c][0]); a1 += ll_val(zw[c][1]); }
            }
            if (hg < 3) {
                sm.red[hg][cp * 2]     = a0;
                sm.red[hg][cp * 2 + 1] = a1;
            }
            __syncthreads();
            if (tid < OCOLS) {
                const int n = mc * OCOLS + tid;
                const float a  = sm.red[0][tid] + sm.red[1][tid];
                const float t  = bf16r(__bfloat162float(x[n]) + bf16r(a));
                const float zz = bf16r(bf16r(sm.red[2][tid]) + __bfloat162float(b2[n]));
                out[n] = __float2bfloat16_rn(t + zz);
            }
            if (mc == 0 && tid == 0) *reinterpret_cast<volatile unsigned*>(&g_epoch) = epoch + 1u;
        }
        DBG_STAMP(3);
    }
}

}

extern "C" void kernel_launch(void* const* d_in, const int* in_sizes, int n_in, void* d_out, int out_size) {
    const __nv_bfloat16* x  = (const __nv_bfloat16*)d_in[0];
    const __nv_bfloat16* kc = (const __nv_bfloat16*)d_in[1];
    const __nv_bfloat16* vc = (const __nv_bfloat16*)d_in[2];
    const __nv_bfloat16* wq = (const __nv_bfloat16*)d_in[3];
    const __nv_bfloat16* wo = (const __nv_bfloat16*)d_in[4];
    const __nv_bfloat16* w1 = (const __nv_bfloat16*)d_in[6];
    const __nv_bfloat16* b1 = (const __nv_bfloat16*)d_in[7];
    const __nv_bfloat16* w2 = (const __nv_bfloat16*)d_in[8];
    const __nv_bfloat16* b2 = (const __nv_bfloat16*)d_in[9];
    __nv_bfloat16* out = (__nv_bfloat16*)d_out;

    static bool attr_set = false;
    if (!attr_set) {
        cudaFuncSetAttribute(fused_decode_kernel, cudaFuncAttributeMaxDynamicSharedMemorySize, (int)sizeof(SmemLayout));
        attr_set = true;
    }
    fused_decode_kernel<<<GRID, NTHREADS, sizeof(SmemLayout)>>>(x, kc, vc, wq, wo, w1, b1, w2, b2, out);
}
```

```cpp
#include <cuda_runtime.h>
#include <cuda_bf16.h>
#include <stdint.h>

namespace {

constexpr int D_MODEL = 640;
constexpr int NHEAD   = 32;
constexpr int DH      = 128;
constexpr int SK      = 16384;
constexpr int FF      = 1728;

#define CFG_TILE 32
#define CFG_NSTAGE 10
#define CFG_DEPTH 4

constexpr int NSPLIT        = 4;
constexpr int TILE          = CFG_TILE;
constexpr int NSTAGE        = CFG_NSTAGE;
constexpr int DEPTH         = CFG_DEPTH;
constexpr int NT_HEAD       = SK / TILE;
constexpr int TILE_BYTES    = TILE * DH * 2;
constexpr int NCONS_WARPS   = 8;
constexpr int NCONS         = NCONS_WARPS * 32;
constexpr int NR            = TILE / NCONS_WARPS / 2;
constexpr int NTHREADS      = NCONS + 32;
constexpr int N_ATTN_CTA    = NHEAD * NSPLIT;
constexpr int N_MLP_CTA     = 4;
constexpr int GRID          = N_ATTN_CTA + N_MLP_CTA;
constexpr int OCOLS         = D_MODEL / NSPLIT;
constexpr int SPIN_LIMIT    = 1 << 22;

constexpr float LOG2E = 1.4426950408889634f;

typedef unsigned long long u64;

__device__ __align__(16) u64 g_qpart[NHEAD][NSPLIT][DH];
__device__ __align__(16) u64 g_part[NHEAD][NSPLIT][DH + 2];
__device__ __align__(16) u64 g_headout[NHEAD][D_MODEL];
__device__ __align__(16) u64 g_mlp_part[N_MLP_CTA][D_MODEL];
__device__ unsigned g_ticket[NHEAD];
__device__ unsigned g_epoch;

#define DBG_STAMP(i) do { } while (0)

struct __align__(128) SmemLayout {
    uint8_t  kbuf[NSTAGE][TILE_BYTES];
    uint8_t  vbuf[NSTAGE][TILE_BYTES];
    uint64_t full_k[NSTAGE];
    uint64_t full_v[NSTAGE];
    uint64_t empty[NSTAGE];
    int      valid[NSTAGE];
    float    xn[D_MODEL];
    float    q[DH];
    float    red[16][OCOLS];
    float    ms[16];
    float    ls[16];
    float    of[DH];
    __align__(16) float red2[5][D_MODEL];
};

__device__ __forceinline__ float bf16r(float x) { return __bfloat162float(__float2bfloat16_rn(x)); }
__device__ __forceinline__ float bf_lo(uint32_t u) { return __uint_as_float(u << 16); }
__device__ __forceinline__ float bf_hi(uint32_t u) { return __uint_as_float(u & 0xffff0000u); }

__device__ __forceinline__ uint32_t smem_u32(const void* p) { return (uint32_t)__cvta_generic_to_shared(p); }
__device__ __forceinline__ void mbar_init(uint64_t* bar, uint32_t count) {
    asm volatile("mbarrier.init.shared::cta.b64 [%0], %1;" ::"r"(smem_u32(bar)), "r"(count) : "memory");
}
__device__ __forceinline__ void mbar_expect_tx(uint64_t* bar, uint32_t bytes) {
    asm volatile("mbarrier.arrive.expect_tx.shared::cta.b64 _, [%0], %1;" ::"r"(smem_u32(bar)), "r"(bytes) : "memory");
}
__device__ __forceinline__ void mbar_arrive(uint64_t* bar) {
    asm volatile("mbarrier.arrive.shared::cta.b64 _, [%0];" ::"r"(smem_u32(bar)) : "memory");
}
__device__ __forceinline__ bool mbar_try_wait(uint64_t* bar, uint32_t parity) {
    uint32_t ok;
    asm volatile(
        "{\n\t.reg .pred p;\n\t"
        "mbarrier.try_wait.parity.shared::cta.b64 p, [%1], %2;\n\t"
        "selp.u32 %0, 1, 0, p;\n\t}"
        : "=r"(ok)
        : "r"(smem_u32(bar)), "r"(parity)
        : "memory");
    return ok != 0;
}
__device__ __forceinline__ void mbar_wait(uint64_t* bar, uint32_t parity) {
    while (!mbar_try_wait(bar, parity)) {
    }
}
__device__ __forceinline__ void bulk_g2s(void* dst, const void* src, uint32_t bytes, uint64_t* bar, uint64_t policy) {
    asm volatile(
        "cp.async.bulk.shared::cluster.global.mbarrier::complete_tx::bytes.L2::cache_hint [%0], [%1], %2, [%3], %4;"
        ::"r"(smem_u32(dst)), "l"(src), "r"(bytes), "r"(smem_u32(bar)), "l"(policy)
        : "memory");
}
__device__ __forceinline__ uint4 ldg_nc(const void* p) {
    uint4 r;
    asm volatile("ld.global.nc.L1::no_allocate.v4.u32 {%0,%1,%2,%3}, [%4];"
                 : "=r"(r.x), "=r"(r.y), "=r"(r.z), "=r"(r.w)
                 : "l"(p));
    return r;
}
__device__ __forceinline__ uint4 lds128(const void* p) {
    uint4 r;
    asm volatile("ld.shared.v4.u32 {%0,%1,%2,%3}, [%4];"
                 : "=r"(r.x), "=r"(r.y), "=r"(r.z), "=r"(r.w)
                 : "r"(smem_u32(p)));
    return r;
}
__device__ __forceinline__ void named_bar_sync(int id, int n) {
    asm volatile("bar.sync %0, %1;" ::"r"(id), "r"(n) : "memory");
}
__device__ __forceinline__ void st_ll(u64* p, float v, unsigned tag) {
    const u64 w = ((u64)tag << 32) | (u64)__float_as_uint(v);
    asm volatile("st.relaxed.gpu.global.b64 [%0], %1;" ::"l"(p), "l"(w) : "memory");
}
__device__ __forceinline__ u64 ld_ll(const u64* p) {
    u64 w;
    asm volatile("ld.relaxed.gpu.global.b64 %0, [%1];" : "=l"(w) : "l"(p) : "memory");
    return w;
}
__device__ __forceinline__ void ld_ll2(const u64* p, u64& a, u64& b) {
    asm volatile("ld.relaxed.gpu.global.v2.b64 {%0,%1}, [%2];" : "=l"(a), "=l"(b) : "l"(p) : "memory");
}
__device__ __forceinline__ bool ll_ok(u64 w, unsigned tag) { return (unsigned)(w >> 32) == tag; }
__device__ __forceinline__ float ll_val(u64 w) { return __uint_as_float((unsigned)w); }

__device__ __forceinline__ void fma8(float* acc, float xv, const uint4& w) {
    acc[0] = fmaf(xv, bf_lo(w.x), acc[0]); acc[1] = fmaf(xv, bf_hi(w.x), acc[1]);
    acc[2] = fmaf(xv, bf_lo(w.y), acc[2]); acc[3] = fmaf(xv, bf_hi(w.y), acc[3]);
    acc[4] = fmaf(xv, bf_lo(w.z), acc[4]); acc[5] = fmaf(xv, bf_hi(w.z), acc[5]);
    acc[6] = fmaf(xv, bf_lo(w.w), acc[6]); acc[7] = fmaf(xv, bf_hi(w.w), acc[7]);
}

__device__ void layernorm_bf16(const float* in, float* out, float* scr, int tid, int nthr, int bar_id) {
    const int lane = tid & 31, wid = tid >> 5, nw = nthr >> 5;
    float s = 0.f;
    for (int i = tid; i < D_MODEL; i += nthr) s += in[i];
#pragma unroll
    for (int o = 16; o > 0; o >>= 1) s += __shfl_xor_sync(0xffffffffu, s, o);
    if (lane == 0) scr[wid] = s;
    named_bar_sync(bar_id, nthr);
    float tot = 0.f;
    for (int w = 0; w < nw; w++) tot += scr[w];
    const float mean = tot * (1.0f / D_MODEL);
    float vs = 0.f;
    for (int i = tid; i < D_MODEL; i += nthr) {
        float d = in[i] - mean;
        vs += d * d;
    }
#pragma unroll
    for (int o = 16; o > 0; o >>= 1) vs += __shfl_xor_sync(0xffffffffu, vs, o);
    if (lane == 0) scr[32 + wid] = vs;
    named_bar_sync(bar_id, nthr);
    float vtot = 0.f;
    for (int w = 0; w < nw; w++) vtot += scr[32 + w];
    const float m_b = bf16r(mean);
    const float v_b = bf16r(vtot * (1.0f / D_MODEL));
    const float den = bf16r(sqrtf(bf16r(v_b + 1e-5f)));
    for (int i = tid; i < D_MODEL; i += nthr) {
        float d = bf16r(in[i] - m_b);
        out[i]  = bf16r(d / den);
    }
    named_bar_sync(bar_id, nthr);
}

__device__ __forceinline__ float gelu_tanh(float x) {
    const float k0 = 0.7978845608028654f, k1 = 0.044715f;
    float inner = k0 * (x + k1 * x * x * x);
    return 0.5f * x * (1.0f + tanhf(inner));
}

__global__ void __launch_bounds__(NTHREADS, 1)
fused_decode_kernel(const __nv_bfloat16* __restrict__ x,
                    const __nv_bfloat16* __restrict__ kc,
                    const __nv_bfloat16* __restrict__ vc,
                    const __nv_bfloat16* __restrict__ wq,
                    const __nv_bfloat16* __restrict__ wo,
                    const __nv_bfloat16* __restrict__ w1,
                    const __nv_bfloat16* __restrict__ b1,
                    const __nv_bfloat16* __restrict__ w2,
                    const __nv_bfloat16* __restrict__ b2,
                    __nv_bfloat16* __restrict__ out) {
    extern __shared__ uint8_t smem_raw[];
    SmemLayout& sm = *reinterpret_cast<SmemLayout*>(smem_raw);
    const int tid  = threadIdx.x;
    const int lane = tid & 31;
    const int wid  = tid >> 5;
    const int cta  = blockIdx.x;
    DBG_STAMP(0);

    const unsigned epoch = *reinterpret_cast<volatile unsigned*>(&g_epoch);
    const unsigned tag   = epoch + 1u;

    if (cta < N_ATTN_CTA) {
        const int h     = cta % NHEAD;
        const int split = cta / NHEAD;

        const uint8_t* kbase = reinterpret_cast<const uint8_t*>(kc) + (size_t)h * SK * (DH * 2);
        const uint8_t* vbase = reinterpret_cast<const uint8_t*>(vc) + (size_t)h * SK * (DH * 2);
        const int l16q = tid & 15;
        const int rgq  = tid >> 4;
        uint4 wqr[10];
        float xr[3];
        if (wid < NCONS_WARPS) {
#pragma unroll
            for (int u = 0; u < 3; u++) {
                const int i = tid + u * NCONS;
                xr[u] = (i < D_MODEL) ? __bfloat162float(x[i]) : 0.f;
            }
            const uint8_t* wbase = reinterpret_cast<const uint8_t*>(wq) + (size_t)h * DH * 2 + l16q * 16;
#pragma unroll
            for (int u = 0; u < 10; u++)
                wqr[u] = ldg_nc(wbase + (size_t)(split * 160 + rgq + 16 * u) * (NHEAD * DH * 2));
        }
        if (tid == NCONS) {
#pragma unroll
            for (int s = 0; s < NSTAGE; s++) {
                mbar_init(&sm.full_k[s], 1);
                mbar_init(&sm.full_v[s], 1);
                mbar_init(&sm.empty[s], NCONS_WARPS);
            }
            asm volatile("fence.mbarrier_init.release.cluster;" ::: "memory");
        }
        __syncthreads();

        if (wid == NCONS_WARPS) {
            if (lane == 0) {
                uint64_t policy;
                asm volatile("createpolicy.fractional.L2::evict_first.b64 %0, 1.0;" : "=l"(policy));
                constexpr unsigned NSTATIC = NSTAGE * NSPLIT;
                const unsigned tbase = epoch * (unsigned)(NT_HEAD - NSTATIC + NSPLIT) - NSTATIC;
                unsigned next = 0;
                for (int it = 0;; it++) {
                    const int s = it % NSTAGE;
                    unsigned t;
                    if (it < NSTAGE) {
                        t = split + NSPLIT * it;
                        if (it == NSTAGE - 1) next = atomicAdd(&g_ticket[h], 1u) - tbase;
                    } else {
                        t = next;
                        if (t < (unsigned)NT_HEAD) next = atomicAdd(&g_ticket[h], 1u) - tbase;
                        mbar_wait(&sm.empty[s], ((it / NSTAGE) - 1) & 1);
                    }
                    if (t >= (unsigned)NT_HEAD) {
                        sm.valid[s] = 0;
                        mbar_arrive(&sm.full_k[s]);
                        break;
                    }
                    if (it >= DEPTH) {
                        const int d = it - DEPTH;
                        mbar_wait(&sm.full_v[d % NSTAGE], (d / NSTAGE) & 1);
                    }
                    sm.valid[s] = 1;
                    mbar_expect_tx(&sm.full_k[s], TILE_BYTES);
                    bulk_g2s(sm.kbuf[s], kbase + (size_t)t * TILE_BYTES, TILE_BYTES, &sm.full_k[s], policy);
                    mbar_expect_tx(&sm.full_v[s], TILE_BYTES);
                    bulk_g2s(sm.vbuf[s], vbase + (size_t)t * TILE_BYTES, TILE_BYTES, &sm.full_v[s], policy);
                }
            }
            return;
        }

#pragma unroll
        for (int u = 0; u < 3; u++) {
            const int i = tid + u * NCONS;
            if (i < D_MODEL) sm.xn[i] = xr[u];
        }
        named_bar_sync(1, NCONS);
        layernorm_bf16(sm.xn, sm.xn, &sm.red[0][0], tid, NCONS, 1);
        DBG_STAMP(4);

        {
            float acc[8];
#pragma unroll
            for (int j = 0; j < 8; j++) acc[j] = 0.f;
#pragma unroll
            for (int u = 0; u < 10; u++) fma8(acc, sm.xn[split * 160 + rgq + 16 * u], wqr[u]);
#pragma unroll
            for (int j = 0; j < 8; j++) sm.red[rgq][l16q * 8 + j] = acc[j];
            DBG_STAMP(5);
            named_bar_sync(1, NCONS);
            if (tid < DH) {
                float s = 0.f;
#pragma unroll
                for (int r = 0; r < 16; r++) s += sm.red[r][tid];
                st_ll(&g_qpart[h][split][tid], s, tag);
                u64 w[NSPLIT];
                int spins = 0;
                for (;;) {
                    bool ok = true;
#pragma unroll
                    for (int i = 0; i < NSPLIT; i++) w[i] = ld_ll(&g_qpart[h][i][tid]);
#pragma unroll
                    for (int i = 0; i < NSPLIT; i++) ok = ok && ll_ok(w[i], tag);
                    if (ok || ++spins > SPIN_LIMIT) break;
                }
                sm.q[tid] = bf16r((ll_val(w[0]) + ll_val(w[1])) + (ll_val(w[2]) + ll_val(w[3])));
            }
            named_bar_sync(1, NCONS);
        }
        DBG_STAMP(1);

        const int half = lane >> 4;
        const int l16  = lane & 15;
        float qf[8];
#pragma unroll
        for (int j = 0; j < 8; j++) qf[j] = sm.q[l16 * 8 + j];

        float m = -INFINITY, l = 0.f;
        float o[8];
#pragma unroll
        for (int j = 0; j < 8; j++) o[j] = 0.f;
        const float scale = 0.08838834764831845f;
        const int row_off = (wid * (2 * NR) + half) * (DH * 2) + l16 * 16;

        int s = 0;
        uint32_t ph = 0;
#pragma unroll 1
        for (;;) {
            mbar_wait(&sm.full_k[s], ph);
            if (*reinterpret_cast<volatile int*>(&sm.valid[s]) == 0) break;
            uint4 kk[NR];
#pragma unroll
            for (int i = 0; i < NR; i++) kk[i] = lds128(sm.kbuf[s] + row_off + i * 2 * (DH * 2));
            float sc[NR];
#pragma unroll
            for (int i = 0; i < NR; i++) {
                float a = qf[0] * bf_lo(kk[i].x);
                a = fmaf(qf[1], bf_hi(kk[i].x), a);
                a = fmaf(qf[2], bf_lo(kk[i].y), a);
                a = fmaf(qf[3], bf_hi(kk[i].y), a);
                a = fmaf(qf[4], bf_lo(kk[i].z), a);
                a = fmaf(qf[5], bf_hi(kk[i].z), a);
                a = fmaf(qf[6], bf_lo(kk[i].w), a);
                a = fmaf(qf[7], bf_hi(kk[i].w), a);
                sc[i] = a;
            }
#pragma unroll
            for (int off = 8; off > 0; off >>= 1) {
#pragma unroll
                for (int i = 0; i < NR; i++) sc[i] += __shfl_xor_sync(0xffffffffu, sc[i], off);
            }
#pragma unroll
            for (int i = 0; i < NR; i++) sc[i] = bf16r(bf16r(sc[i]) * scale);
            float mnew = m;
#pragma unroll
            for (int i = 0; i < NR; i++) mnew = fmaxf(mnew, sc[i]);
            const float corr = exp2f((m - mnew) * LOG2E);
            float p[NR];
            float ps = 0.f;
#pragma unroll
            for (int i = 0; i < NR; i++) {
                p[i] = exp2f((sc[i] - mnew) * LOG2E);
                ps += p[i];
            }
            l = l * corr + ps;
            m = mnew;
#pragma unroll
            for (int j = 0; j < 8; j++) o[j] *= corr;

            mbar_wait(&sm.full_v[s], ph);
            uint4 vv[NR];
#pragma unroll
            for (int i = 0; i < NR; i++) vv[i] = lds128(sm.vbuf[s] + row_off + i * 2 * (DH * 2));
#pragma unroll
            for (int i = 0; i < NR; i++) fma8(o, p[i], vv[i]);
            __syncwarp();
            if (lane == 0) mbar_arrive(&sm.empty[s]);
            if (++s == NSTAGE) { s = 0; ph ^= 1; }
        }
        DBG_STAMP(2);

        const int cgo = tid % 20;
        const int rgo = tid / 20;
        uint4 wor[11];
        if (rgo < 12) {
            const uint8_t* wbase = reinterpret_cast<const uint8_t*>(wo) + (size_t)h * DH * (D_MODEL * 2) + split * (OCOLS * 2) + cgo * 16;
#pragma unroll
            for (int u = 0; u < 11; u++) {
                const int row = rgo + 12 * u;
                if (u < 10 || row < DH) wor[u] = ldg_nc(wbase + (size_t)row * (D_MODEL * 2));
            }
        }

        {
            const int st = wid * 2 + half;
#pragma unroll
            for (int j = 0; j < 8; j++) sm.red[st][l16 * 8 + j] = o[j];
            if (l16 == 0) {
                sm.ms[st] = m;
                sm.ls[st] = l;
            }
            named_bar_sync(1, NCONS);
            if (tid < DH) {
                float M = sm.ms[0];
#pragma unroll
                for (int i = 1; i < 16; i++) M = fmaxf(M, sm.ms[i]);
                float L = 0.f, O = 0.f;
                if (M > -INFINITY) {
#pragma unroll
                    for (int i = 0; i < 16; i++) {
                        const float w = exp2f((sm.ms[i] - M) * LOG2E);
                        L += w * sm.ls[i];
                        O += w * sm.red[i][tid];
                    }
                }
                st_ll(&g_part[h][split][tid], O, tag);
                if (tid == 0) {
                    st_ll(&g_part[h][split][DH], M, tag);
                    st_ll(&g_part[h][split][DH + 1], L, tag);
                }
                u64 wo_[NSPLIT], wm[NSPLIT], wl[NSPLIT];
                int spins = 0;
                for (;;) {
                    bool ok = true;
#pragma unroll
                    for (int i = 0; i < NSPLIT; i++) {
                        wo_[i] = ld_ll(&g_part[h][i][tid]);
                        ld_ll2(&g_part[h][i][DH], wm[i], wl[i]);
                    }
#pragma unroll
                    for (int i = 0; i < NSPLIT; i++) ok = ok && ll_ok(wo_[i], tag) && ll_ok(wm[i], tag) && ll_ok(wl[i], tag);
                    if (ok || ++spins > SPIN_LIMIT) break;
                }
                float MM = -INFINITY;
#pragma unroll
                for (int i = 0; i < NSPLIT; i++) MM = fmaxf(MM, ll_val(wm[i]));
                float LL = 0.f, OO = 0.f;
#pragma unroll
                for (int i = 0; i < NSPLIT; i++) {
                    const float mi = ll_val(wm[i]);
                    const float w  = (mi > -INFINITY) ? exp2f((mi - MM) * LOG2E) : 0.f;
                    LL += w * ll_val(wl[i]);
                    OO += w * ll_val(wo_[i]);
                }
                sm.of[tid] = bf16r(OO / LL);
            }
            named_bar_sync(1, NCONS);
        }
        DBG_STAMP(7);

        {
            if (rgo < 12) {
                float acc[8];
#pragma unroll
                for (int j = 0; j < 8; j++) acc[j] = 0.f;
#pragma unroll
                for (int u = 0; u < 11; u++) {
                    const int row = rgo + 12 * u;
                    if (u < 10 || row < DH) fma8(acc, sm.of[row], wor[u]);
                }
#pragma unroll
                for (int j = 0; j < 8; j++) sm.red[rgo][cgo * 8 + j] = acc[j];
            }
            named_bar_sync(1, NCONS);
            if (tid < OCOLS) {
                float a = 0.f;
#pragma unroll
                for (int r = 0; r < 12; r++) a += sm.red[r][tid];
                st_ll(&g_headout[h][split * OCOLS + tid], a, tag);
            }
        }
        DBG_STAMP(6);

        {
            constexpr int FC = D_MODEL / N_ATTN_CTA;
            constexpr int NSRC = NHEAD + N_MLP_CTA;
            const int src = tid / FC, c = tid % FC;
            const int n = cta * FC + c;
            if (src < NSRC) {
                const u64* p = (src < NHEAD) ? &g_headout[src][n] : &g_mlp_part[src - NHEAD][n];
                u64 w = ld_ll(p);
                int spins = 0;
                while (!ll_ok(w, tag) && ++spins < SPIN_LIMIT) w = ld_ll(p);
                sm.red2[0][src * FC + c] = ll_val(w);
            }
            named_bar_sync(1, NCONS);
            if (tid < FC) {
                float a = 0.f, z = 0.f;
#pragma unroll
                for (int hh = 0; hh < NHEAD; hh++) a += sm.red2[0][hh * FC + tid];
#pragma unroll
                for (int cc = 0; cc < N_MLP_CTA; cc++) z += sm.red2[0][(NHEAD + cc) * FC + tid];
                const int nn = cta * FC + tid;
                const float t  = bf16r(__bfloat162float(x[nn]) + bf16r(a));
                const float zz = bf16r(bf16r(z) + __bfloat162float(b2[nn]));
                out[nn] = __float2bfloat16_rn(t + zz);
            }
            if (cta == 0 && tid == 0) *reinterpret_cast<volatile unsigned*>(&g_epoch) = epoch + 1u;
        }
        DBG_STAMP(3);
        return;
    }

    {
        const int mc = cta - N_ATTN_CTA;
        for (int i = tid; i < D_MODEL; i += NTHREADS) sm.xn[i] = __bfloat162float(x[i]);
        named_bar_sync(1, NTHREADS);
        layernorm_bf16(sm.xn, sm.xn, &sm.red[0][0], tid, NTHREADS, 1);
        layernorm_bf16(sm.xn, sm.xn, &sm.red[0][0], tid, NTHREADS, 1);

        constexpr int CPC = FF / N_MLP_CTA;
        float* hs = reinterpret_cast<float*>(sm.vbuf);
        {
            constexpr int NCG = CPC / 8;
            constexpr int NRG = 5;
            const int cg = tid % NCG, rg = tid / NCG;
            if (rg < NRG) {
                float acc[8];
#pragma unroll
                for (int j = 0; j < 8; j++) acc[j] = 0.f;
                const uint8_t* wbase = reinterpret_cast<const uint8_t*>(w1) + (size_t)(mc * CPC + cg * 8) * 2;
#pragma unroll 1
                for (int it = 0; it < 8; it++) {
                    uint4 w[16];
#pragma unroll
                    for (int u = 0; u < 16; u++) w[u] = ldg_nc(wbase + (size_t)(rg * 128 + it * 16 + u) * (FF * 2));
#pragma unroll
                    for (int u = 0; u < 16; u++) fma8(acc, sm.xn[rg * 128 + it * 16 + u], w[u]);
                }
#pragma unroll
                for (int j = 0; j < 8; j++) sm.red2[rg][cg * 8 + j] = acc[j];
            }
            __syncthreads();
            for (int c = tid; c < CPC; c += NTHREADS) {
                float s = 0.f;
#pragma unroll
                for (int r = 0; r < NRG; r++) s += sm.red2[r][c];
                const int f = mc * CPC + c;
                float u = bf16r(bf16r(s) + __bfloat162float(b1[f]));
                hs[c] = bf16r(gelu_tanh(u));
            }
            __syncthreads();
        }
        DBG_STAMP(1);
        {
            const int cg = tid % 80, rgp = tid / 80;
            if (rgp < 3) {
                float acc[8];
#pragma unroll
                for (int j = 0; j < 8; j++) acc[j] = 0.f;
                const uint8_t* wbase = reinterpret_cast<const uint8_t*>(w2) + (size_t)(mc * CPC) * (D_MODEL * 2) + cg * 16;
#pragma unroll 1
                for (int it = 0; it < 9; it++) {
                    uint4 w[16];
#pragma unroll
                    for (int u = 0; u < 16; u++) w[u] = ldg_nc(wbase + (size_t)(rgp * 144 + it * 16 + u) * (D_MODEL * 2));
#pragma unroll
                    for (int u = 0; u < 16; u++) fma8(acc, hs[rgp * 144 + it * 16 + u], w[u]);
                }
#pragma unroll
                for (int j = 0; j < 8; j++) sm.red2[rgp][cg * 8 + j] = acc[j];
            }
            __syncthreads();
            for (int n = tid; n < D_MODEL; n += NTHREADS)
                st_ll(&g_mlp_part[mc][n], sm.red2[0][n] + sm.red2[1][n] + sm.red2[2][n], tag);
        }
        DBG_STAMP(2);

        DBG_STAMP(3);
    }
}

}

extern "C" void kernel_launch(void* const* d_in, const int* in_sizes, int n_in, void* d_out, int out_size) {
    const __nv_bfloat16* x  = (const __nv_bfloat16*)d_in[0];
    const __nv_bfloat16* kc = (const __nv_bfloat16*)d_in[1];
    const __nv_bfloat16* vc = (const __nv_bfloat16*)d_in[2];
    const __nv_bfloat16* wq = (const __nv_bfloat16*)d_in[3];
    const __nv_bfloat16* wo = (const __nv_bfloat16*)d_in[4];
    const __nv_bfloat16* w1 = (const __nv_bfloat16*)d_in[6];
    const __nv_bfloat16* b1 = (const __nv_bfloat16*)d_in[7];
    const __nv_bfloat16* w2 = (const __nv_bfloat16*)d_in[8];
    const __nv_bfloat16* b2 = (const __nv_bfloat16*)d_in[9];
    __nv_bfloat16* out = (__nv_bfloat16*)d_out;

    static bool attr_set = false;
    if (!attr_set) {
        cudaFuncSetAttribute(fused_decode_kernel, cudaFuncAttributeMaxDynamicSharedMemorySize, (int)sizeof(SmemLayout));
        attr_set = true;
    }
    fused_decode_kernel<<<GRID, NTHREADS, sizeof(SmemLayout)>>>(x, kc, vc, wq, wo, w1, b1, w2, b2, out);
}
```

```cpp
#include <cuda_runtime.h>
#include <cuda_bf16.h>
#include <stdint.h>

namespace {

constexpr int D_MODEL = 640;
constexpr int NHEAD   = 32;
constexpr int DH      = 128;
constexpr int SK      = 16384;
constexpr int FF      = 1728;

#define CFG_TILE 32
#define CFG_NSTAGE 10
#define CFG_SLEEP 100
#define CFG_DEPTH 4

constexpr int NSPLIT        = 4;
constexpr int TILE          = CFG_TILE;
constexpr int NSTAGE        = CFG_NSTAGE;
constexpr int DEPTH         = CFG_DEPTH;
constexpr int NT_HEAD       = SK / TILE;
constexpr int TILE_BYTES    = TILE * DH * 2;
constexpr int NCONS_WARPS   = 8;
constexpr int NCONS         = NCONS_WARPS * 32;
constexpr int NR            = TILE / NCONS_WARPS / 2;
constexpr int NTHREADS      = NCONS + 32;
constexpr int N_ATTN_CTA    = NHEAD * NSPLIT;
constexpr int N_MLP_CTA     = 4;
constexpr int GRID          = N_ATTN_CTA + N_MLP_CTA;
constexpr int OCOLS         = D_MODEL / NSPLIT;
constexpr int SPIN_LIMIT    = 1 << 22;

constexpr float LOG2E = 1.4426950408889634f;

typedef unsigned long long u64;

__device__ __align__(16) u64 g_qpart[NHEAD][NSPLIT][DH];
__device__ __align__(16) u64 g_part[NHEAD][NSPLIT][DH + 2];
__device__ __align__(16) u64 g_headout[NHEAD][D_MODEL];
__device__ __align__(16) u64 g_mlp_part[N_MLP_CTA][D_MODEL];
__device__ unsigned g_ticket[NHEAD];
__device__ unsigned g_epoch;

#define DBG_STAMP(i) do { } while (0)

struct __align__(128) SmemLayout {
    uint8_t  kbuf[NSTAGE][TILE_BYTES];
    uint8_t  vbuf[NSTAGE][TILE_BYTES];
    uint64_t full_k[NSTAGE];
    uint64_t full_v[NSTAGE];
    uint64_t empty[NSTAGE];
    int      valid[NSTAGE];
    int      ending;
    float    xn[D_MODEL];
    float    q[DH];
    float    red[16][OCOLS];
    float    ms[16];
    float    ls[16];
    float    of[DH];
    __align__(16) float red2[5][D_MODEL];
};

__device__ __forceinline__ float bf16r(float x) { return __bfloat162float(__float2bfloat16_rn(x)); }
__device__ __forceinline__ float bf_lo(uint32_t u) { return __uint_as_float(u << 16); }
__device__ __forceinline__ float bf_hi(uint32_t u) { return __uint_as_float(u & 0xffff0000u); }

__device__ __forceinline__ uint32_t smem_u32(const void* p) { return (uint32_t)__cvta_generic_to_shared(p); }
__device__ __forceinline__ void mbar_init(uint64_t* bar, uint32_t count) {
    asm volatile("mbarrier.init.shared::cta.b64 [%0], %1;" ::"r"(smem_u32(bar)), "r"(count) : "memory");
}
__device__ __forceinline__ void mbar_expect_tx(uint64_t* bar, uint32_t bytes) {
    asm volatile("mbarrier.arrive.expect_tx.shared::cta.b64 _, [%0], %1;" ::"r"(smem_u32(bar)), "r"(bytes) : "memory");
}
__device__ __forceinline__ void mbar_arrive(uint64_t* bar) {
    asm volatile("mbarrier.arrive.shared::cta.b64 _, [%0];" ::"r"(smem_u32(bar)) : "memory");
}
__device__ __forceinline__ bool mbar_try_wait(uint64_t* bar, uint32_t parity) {
    uint32_t ok;
    asm volatile(
        "{\n\t.reg .pred p;\n\t"
        "mbarrier.try_wait.parity.shared::cta.b64 p, [%1], %2;\n\t"
        "selp.u32 %0, 1, 0, p;\n\t}"
        : "=r"(ok)
        : "r"(smem_u32(bar)), "r"(parity)
        : "memory");
    return ok != 0;
}
__device__ __forceinline__ void mbar_wait(uint64_t* bar, uint32_t parity) {
    while (!mbar_try_wait(bar, parity)) {
    }
}
__device__ __forceinline__ void bulk_g2s(void* dst, const void* src, uint32_t bytes, uint64_t* bar, uint64_t policy) {
    asm volatile(
        "cp.async.bulk.shared::cluster.global.mbarrier::complete_tx::bytes.L2::cache_hint [%0], [%1], %2, [%3], %4;"
        ::"r"(smem_u32(dst)), "l"(src), "r"(bytes), "r"(smem_u32(bar)), "l"(policy)
        : "memory");
}
__device__ __forceinline__ uint4 ldg_nc(const void* p) {
    uint4 r;
    asm volatile("ld.global.nc.L1::no_allocate.v4.u32 {%0,%1,%2,%3}, [%4];"
                 : "=r"(r.x), "=r"(r.y), "=r"(r.z), "=r"(r.w)
                 : "l"(p));
    return r;
}
__device__ __forceinline__ uint4 lds128(const void* p) {
    uint4 r;
    asm volatile("ld.shared.v4.u32 {%0,%1,%2,%3}, [%4];"
                 : "=r"(r.x), "=r"(r.y), "=r"(r.z), "=r"(r.w)
                 : "r"(smem_u32(p)));
    return r;
}
__device__ __forceinline__ void named_bar_sync(int id, int n) {
    asm volatile("bar.sync %0, %1;" ::"r"(id), "r"(n) : "memory");
}
__device__ __forceinline__ void st_ll(u64* p, float v, unsigned tag) {
    const u64 w = ((u64)tag << 32) | (u64)__float_as_uint(v);
    asm volatile("st.relaxed.gpu.global.b64 [%0], %1;" ::"l"(p), "l"(w) : "memory");
}
__device__ __forceinline__ u64 ld_ll(const u64* p) {
    u64 w;
    asm volatile("ld.relaxed.gpu.global.b64 %0, [%1];" : "=l"(w) : "l"(p) : "memory");
    return w;
}
__device__ __forceinline__ void ld_ll2(const u64* p, u64& a, u64& b) {
    asm volatile("ld.relaxed.gpu.global.v2.b64 {%0,%1}, [%2];" : "=l"(a), "=l"(b) : "l"(p) : "memory");
}
__device__ __forceinline__ bool ll_ok(u64 w, unsigned tag) { return (unsigned)(w >> 32) == tag; }
__device__ __forceinline__ float ll_val(u64 w) { return __uint_as_float((unsigned)w); }

__device__ __forceinline__ void fma8(float* acc, float xv, const uint4& w) {
    acc[0] = fmaf(xv, bf_lo(w.x), acc[0]); acc[1] = fmaf(xv, bf_hi(w.x), acc[1]);
    acc[2] = fmaf(xv, bf_lo(w.y), acc[2]); acc[3] = fmaf(xv, bf_hi(w.y), acc[3]);
    acc[4] = fmaf(xv, bf_lo(w.z), acc[4]); acc[5] = fmaf(xv, bf_hi(w.z), acc[5]);
    acc[6] = fmaf(xv, bf_lo(w.w), acc[6]); acc[7] = fmaf(xv, bf_hi(w.w), acc[7]);
}

__device__ void layernorm_bf16(const float* in, float* out, float* scr, int tid, int nthr, int bar_id) {
    const int lane = tid & 31, wid = tid >> 5, nw = nthr >> 5;
    float s = 0.f;
    for (int i = tid; i < D_MODEL; i += nthr) s += in[i];
#pragma unroll
    for (int o = 16; o > 0; o >>= 1) s += __shfl_xor_sync(0xffffffffu, s, o);
    if (lane == 0) scr[wid] = s;
    named_bar_sync(bar_id, nthr);
    float tot = 0.f;
    for (int w = 0; w < nw; w++) tot += scr[w];
    const float mean = tot * (1.0f / D_MODEL);
    float vs = 0.f;
    for (int i = tid; i < D_MODEL; i += nthr) {
        float d = in[i] - mean;
        vs += d * d;
    }
#pragma unroll
    for (int o = 16; o > 0; o >>= 1) vs += __shfl_xor_sync(0xffffffffu, vs, o);
    if (lane == 0) scr[32 + wid] = vs;
    named_bar_sync(bar_id, nthr);
    float vtot = 0.f;
    for (int w = 0; w < nw; w++) vtot += scr[32 + w];
    const float m_b = bf16r(mean);
    const float v_b = bf16r(vtot * (1.0f / D_MODEL));
    const float den = bf16r(sqrtf(bf16r(v_b + 1e-5f)));
    for (int i = tid; i < D_MODEL; i += nthr) {
        float d = bf16r(in[i] - m_b);
        out[i]  = bf16r(d / den);
    }
    named_bar_sync(bar_id, nthr);
}

__device__ __forceinline__ float gelu_tanh(float x) {
    const float k0 = 0.7978845608028654f, k1 = 0.044715f;
    float inner = k0 * (x + k1 * x * x * x);
    return 0.5f * x * (1.0f + tanhf(inner));
}

__global__ void __launch_bounds__(NTHREADS, 1)
fused_decode_kernel(const __nv_bfloat16* __restrict__ x,
                    const __nv_bfloat16* __restrict__ kc,
                    const __nv_bfloat16* __restrict__ vc,
                    const __nv_bfloat16* __restrict__ wq,
                    const __nv_bfloat16* __restrict__ wo,
                    const __nv_bfloat16* __restrict__ w1,
                    const __nv_bfloat16* __restrict__ b1,
                    const __nv_bfloat16* __restrict__ w2,
                    const __nv_bfloat16* __restrict__ b2,
                    __nv_bfloat16* __restrict__ out) {
    extern __shared__ uint8_t smem_raw[];
    SmemLayout& sm = *reinterpret_cast<SmemLayout*>(smem_raw);
    const int tid  = threadIdx.x;
    const int lane = tid & 31;
    const int wid  = tid >> 5;
    const int cta  = blockIdx.x;
    DBG_STAMP(0);

    const unsigned epoch = *reinterpret_cast<volatile unsigned*>(&g_epoch);
    const unsigned tag   = epoch + 1u;

    if (cta < N_ATTN_CTA) {
        const int h     = cta % NHEAD;
        const int split = cta / NHEAD;

        const uint8_t* kbase = reinterpret_cast<const uint8_t*>(kc) + (size_t)h * SK * (DH * 2);
        const uint8_t* vbase = reinterpret_cast<const uint8_t*>(vc) + (size_t)h * SK * (DH * 2);
        const int l16q = tid & 15;
        const int rgq  = tid >> 4;
        uint4 wqr[10];
        float xr[3];
        if (wid < NCONS_WARPS) {
#pragma unroll
            for (int u = 0; u < 3; u++) {
                const int i = tid + u * NCONS;
                xr[u] = (i < D_MODEL) ? __bfloat162float(x[i]) : 0.f;
            }
            const uint8_t* wbase = reinterpret_cast<const uint8_t*>(wq) + (size_t)h * DH * 2 + l16q * 16;
#pragma unroll
            for (int u = 0; u < 10; u++)
                wqr[u] = ldg_nc(wbase + (size_t)(split * 160 + rgq + 16 * u) * (NHEAD * DH * 2));
        }
        if (tid == NCONS) {
#pragma unroll
            for (int s = 0; s < NSTAGE; s++) {
                mbar_init(&sm.full_k[s], 1);
                mbar_init(&sm.full_v[s], 1);
                mbar_init(&sm.empty[s], NCONS_WARPS);
            }
            asm volatile("fence.mbarrier_init.release.cluster;" ::: "memory");
            sm.ending = 0;
        }
        __syncthreads();

        if (wid == NCONS_WARPS) {
            if (lane == 0) {
                uint64_t policy;
                asm volatile("createpolicy.fractional.L2::evict_first.b64 %0, 1.0;" : "=l"(policy));
                constexpr unsigned NSTATIC = NSTAGE * NSPLIT;
                const unsigned tbase = epoch * (unsigned)(NT_HEAD - NSTATIC + NSPLIT) - NSTATIC;
                unsigned next = 0;
                for (int it = 0;; it++) {
                    const int s = it % NSTAGE;
                    unsigned t;
                    if (it < NSTAGE) {
                        t = split + NSPLIT * it;
                        if (it == NSTAGE - 1) next = atomicAdd(&g_ticket[h], 1u) - tbase;
                    } else {
                        t = next;
                        if (t < (unsigned)NT_HEAD) next = atomicAdd(&g_ticket[h], 1u) - tbase;
                        else *reinterpret_cast<volatile int*>(&sm.ending) = 1;
                        mbar_wait(&sm.empty[s], ((it / NSTAGE) - 1) & 1);
                    }
                    if (t >= (unsigned)NT_HEAD) {
                        sm.valid[s] = 0;
                        mbar_arrive(&sm.full_k[s]);
                        break;
                    }
                    if (it >= DEPTH) {
                        const int d = it - DEPTH;
                        mbar_wait(&sm.full_v[d % NSTAGE], (d / NSTAGE) & 1);
                    }
                    sm.valid[s] = 1;
                    mbar_expect_tx(&sm.full_k[s], TILE_BYTES);
                    bulk_g2s(sm.kbuf[s], kbase + (size_t)t * TILE_BYTES, TILE_BYTES, &sm.full_k[s], policy);
                    mbar_expect_tx(&sm.full_v[s], TILE_BYTES);
                    bulk_g2s(sm.vbuf[s], vbase + (size_t)t * TILE_BYTES, TILE_BYTES, &sm.full_v[s], policy);
                }
            }
            return;
        }

#pragma unroll
        for (int u = 0; u < 3; u++) {
            const int i = tid + u * NCONS;
            if (i < D_MODEL) sm.xn[i] = xr[u];
        }
        named_bar_sync(1, NCONS);
        layernorm_bf16(sm.xn, sm.xn, &sm.red[0][0], tid, NCONS, 1);
        DBG_STAMP(4);

        {
            float acc[8];
#pragma unroll
            for (int j = 0; j < 8; j++) acc[j] = 0.f;
#pragma unroll
            for (int u = 0; u < 10; u++) fma8(acc, sm.xn[split * 160 + rgq + 16 * u], wqr[u]);
#pragma unroll
            for (int j = 0; j < 8; j++) sm.red[rgq][l16q * 8 + j] = acc[j];
            DBG_STAMP(5);
            named_bar_sync(1, NCONS);
            if (tid < DH) {
                float s = 0.f;
#pragma unroll
                for (int r = 0; r < 16; r++) s += sm.red[r][tid];
                st_ll(&g_qpart[h][split][tid], s, tag);
                u64 w[NSPLIT];
                int spins = 0;
                for (;;) {
                    bool ok = true;
#pragma unroll
                    for (int i = 0; i < NSPLIT; i++) w[i] = ld_ll(&g_qpart[h][i][tid]);
#pragma unroll
                    for (int i = 0; i < NSPLIT; i++) ok = ok && ll_ok(w[i], tag);
                    if (ok || ++spins > SPIN_LIMIT) break;
                }
                sm.q[tid] = bf16r((ll_val(w[0]) + ll_val(w[1])) + (ll_val(w[2]) + ll_val(w[3])));
            }
            named_bar_sync(1, NCONS);
        }
        DBG_STAMP(1);

        const int half = lane >> 4;
        const int l16  = lane & 15;
        float qf[8];
#pragma unroll
        for (int j = 0; j < 8; j++) qf[j] = sm.q[l16 * 8 + j];

        float m = -INFINITY, l = 0.f;
        float o[8];
#pragma unroll
        for (int j = 0; j < 8; j++) o[j] = 0.f;
        const float scale = 0.08838834764831845f;
        const int row_off = (wid * (2 * NR) + half) * (DH * 2) + l16 * 16;

        const int cgo = tid % 20;
        const int rgo = tid / 20;
        uint4 wor[11];
        bool wo_loaded = false;
        auto load_wo = [&]() {
            wo_loaded = true;
            if (rgo < 12) {
                const uint8_t* wbase = reinterpret_cast<const uint8_t*>(wo) + (size_t)h * DH * (D_MODEL * 2) + split * (OCOLS * 2) + cgo * 16;
#pragma unroll
                for (int u = 0; u < 11; u++) {
                    const int row = rgo + 12 * u;
                    if (u < 10 || row < DH) wor[u] = ldg_nc(wbase + (size_t)row * (D_MODEL * 2));
                }
            }
        };

        int s = 0;
        uint32_t ph = 0;
#pragma unroll 1
        for (;;) {
            if (!wo_loaded && *reinterpret_cast<volatile int*>(&sm.ending) != 0) load_wo();
            mbar_wait(&sm.full_k[s], ph);
            if (*reinterpret_cast<volatile int*>(&sm.valid[s]) == 0) break;
            uint4 kk[NR];
#pragma unroll
            for (int i = 0; i < NR; i++) kk[i] = lds128(sm.kbuf[s] + row_off + i * 2 * (DH * 2));
            float sc[NR];
#pragma unroll
            for (int i = 0; i < NR; i++) {
                float a = qf[0] * bf_lo(kk[i].x);
                a = fmaf(qf[1], bf_hi(kk[i].x), a);
                a = fmaf(qf[2], bf_lo(kk[i].y), a);
                a = fmaf(qf[3], bf_hi(kk[i].y), a);
                a = fmaf(qf[4], bf_lo(kk[i].z), a);
                a = fmaf(qf[5], bf_hi(kk[i].z), a);
                a = fmaf(qf[6], bf_lo(kk[i].w), a);
                a = fmaf(qf[7], bf_hi(kk[i].w), a);
                sc[i] = a;
            }
#pragma unroll
            for (int off = 8; off > 0; off >>= 1) {
#pragma unroll
                for (int i = 0; i < NR; i++) sc[i] += __shfl_xor_sync(0xffffffffu, sc[i], off);
            }
#pragma unroll
            for (int i = 0; i < NR; i++) sc[i] = bf16r(bf16r(sc[i]) * scale);
            float mnew = m;
#pragma unroll
            for (int i = 0; i < NR; i++) mnew = fmaxf(mnew, sc[i]);
            const float corr = exp2f((m - mnew) * LOG2E);
            float p[NR];
            float ps = 0.f;
#pragma unroll
            for (int i = 0; i < NR; i++) {
                p[i] = exp2f((sc[i] - mnew) * LOG2E);
                ps += p[i];
            }
            l = l * corr + ps;
            m = mnew;
#pragma unroll
            for (int j = 0; j < 8; j++) o[j] *= corr;

            mbar_wait(&sm.full_v[s], ph);
            uint4 vv[NR];
#pragma unroll
            for (int i = 0; i < NR; i++) vv[i] = lds128(sm.vbuf[s] + row_off + i * 2 * (DH * 2));
#pragma unroll
            for (int i = 0; i < NR; i++) fma8(o, p[i], vv[i]);
            __syncwarp();
            if (lane == 0) mbar_arrive(&sm.empty[s]);
            if (++s == NSTAGE) { s = 0; ph ^= 1; }
        }
        DBG_STAMP(2);

        if (!wo_loaded) load_wo();

        {
            const int st = wid * 2 + half;
#pragma unroll
            for (int j = 0; j < 8; j++) sm.red[st][l16 * 8 + j] = o[j];
            if (l16 == 0) {
                sm.ms[st] = m;
                sm.ls[st] = l;
            }
            named_bar_sync(1, NCONS);
            if (tid < DH) {
                float M = sm.ms[0];
#pragma unroll
                for (int i = 1; i < 16; i++) M = fmaxf(M, sm.ms[i]);
                float L = 0.f, O = 0.f;
                if (M > -INFINITY) {
#pragma unroll
                    for (int i = 0; i < 16; i++) {
                        const float w = exp2f((sm.ms[i] - M) * LOG2E);
                        L += w * sm.ls[i];
                        O += w * sm.red[i][tid];
                    }
                }
                st_ll(&g_part[h][split][tid], O, tag);
                if (tid == 0) {
                    st_ll(&g_part[h][split][DH], M, tag);
                    st_ll(&g_part[h][split][DH + 1], L, tag);
                }
                u64 wo_[NSPLIT], wm[NSPLIT], wl[NSPLIT];
                int spins = 0;
                for (;;) {
                    bool ok = true;
#pragma unroll
                    for (int i = 0; i < NSPLIT; i++) {
                        wo_[i] = ld_ll(&g_part[h][i][tid]);
                        ld_ll2(&g_part[h][i][DH], wm[i], wl[i]);
                    }
#pragma unroll
                    for (int i = 0; i < NSPLIT; i++) ok = ok && ll_ok(wo_[i], tag) && ll_ok(wm[i], tag) && ll_ok(wl[i], tag);
                    if (ok || ++spins > SPIN_LIMIT) break;
                }
                float MM = -INFINITY;
#pragma unroll
                for (int i = 0; i < NSPLIT; i++) MM = fmaxf(MM, ll_val(wm[i]));
                float LL = 0.f, OO = 0.f;
#pragma unroll
                for (int i = 0; i < NSPLIT; i++) {
                    const float mi = ll_val(wm[i]);
                    const float w  = (mi > -INFINITY) ? exp2f((mi - MM) * LOG2E) : 0.f;
                    LL += w * ll_val(wl[i]);
                    OO += w * ll_val(wo_[i]);
                }
                sm.of[tid] = bf16r(OO / LL);
            }
            named_bar_sync(1, NCONS);
        }
        DBG_STAMP(7);

        {
            if (rgo < 12) {
                float acc[8];
#pragma unroll
                for (int j = 0; j < 8; j++) acc[j] = 0.f;
#pragma unroll
                for (int u = 0; u < 11; u++) {
                    const int row = rgo + 12 * u;
                    if (u < 10 || row < DH) fma8(acc, sm.of[row], wor[u]);
                }
#pragma unroll
                for (int j = 0; j < 8; j++) sm.red[rgo][cgo * 8 + j] = acc[j];
            }
            named_bar_sync(1, NCONS);
            if (tid < OCOLS) {
                float a = 0.f;
#pragma unroll
                for (int r = 0; r < 12; r++) a += sm.red[r][tid];
                st_ll(&g_headout[h][split * OCOLS + tid], a, tag);
            }
        }
        DBG_STAMP(6);

        {
            constexpr int FC = D_MODEL / N_ATTN_CTA;
            constexpr int NSRC = NHEAD + N_MLP_CTA;
            const int src = tid / FC, c = tid % FC;
            const int n = cta * FC + c;
            if (src < NSRC) {
                const u64* p = (src < NHEAD) ? &g_headout[src][n] : &g_mlp_part[src - NHEAD][n];
                u64 w = ld_ll(p);
                int spins = 0;
                while (!ll_ok(w, tag) && ++spins < SPIN_LIMIT) { __nanosleep(CFG_SLEEP); w = ld_ll(p); }
                sm.red2[0][src * FC + c] = ll_val(w);
            }
            named_bar_sync(1, NCONS);
            if (tid < FC) {
                float a = 0.f, z = 0.f;
#pragma unroll
                for (int hh = 0; hh < NHEAD; hh++) a += sm.red2[0][hh * FC + tid];
#pragma unroll
                for (int cc = 0; cc < N_MLP_CTA; cc++) z += sm.red2[0][(NHEAD + cc) * FC + tid];
                const int nn = cta * FC + tid;
                const float t  = bf16r(__bfloat162float(x[nn]) + bf16r(a));
                const float zz = bf16r(bf16r(z) + __bfloat162float(b2[nn]));
                out[nn] = __float2bfloat16_rn(t + zz);
            }
            if (cta == 0 && tid == 0) *reinterpret_cast<volatile unsigned*>(&g_epoch) = epoch + 1u;
        }
        DBG_STAMP(3);
        return;
    }

    {
        const int mc = cta - N_ATTN_CTA;
        for (int i = tid; i < D_MODEL; i += NTHREADS) sm.xn[i] = __bfloat162float(x[i]);
        named_bar_sync(1, NTHREADS);
        layernorm_bf16(sm.xn, sm.xn, &sm.red[0][0], tid, NTHREADS, 1);
        layernorm_bf16(sm.xn, sm.xn, &sm.red[0][0], tid, NTHREADS, 1);

        constexpr int CPC = FF / N_MLP_CTA;
        float* hs = reinterpret_cast<float*>(sm.vbuf);
        {
            constexpr int NCG = CPC / 8;
            constexpr int NRG = 5;
            const int cg = tid % NCG, rg = tid / NCG;
            if (rg < NRG) {
                float acc[8];
#pragma unroll
                for (int j = 0; j < 8; j++) acc[j] = 0.f;
                const uint8_t* wbase = reinterpret_cast<const uint8_t*>(w1) + (size_t)(mc * CPC + cg * 8) * 2;
#pragma unroll 1
                for (int it = 0; it < 8; it++) {
                    uint4 w[16];
#pragma unroll
                    for (int u = 0; u < 16; u++) w[u] = ldg_nc(wbase + (size_t)(rg * 128 + it * 16 + u) * (FF * 2));
#pragma unroll
                    for (int u = 0; u < 16; u++) fma8(acc, sm.xn[rg * 128 + it * 16 + u], w[u]);
                }
#pragma unroll
                for (int j = 0; j < 8; j++) sm.red2[rg][cg * 8 + j] = acc[j];
            }
            __syncthreads();
            for (int c = tid; c < CPC; c += NTHREADS) {
                float s = 0.f;
#pragma unroll
                for (int r = 0; r < NRG; r++) s += sm.red2[r][c];
                const int f = mc * CPC + c;
                float u = bf16r(bf16r(s) + __bfloat162float(b1[f]));
                hs[c] = bf16r(gelu_tanh(u));
            }
            __syncthreads();
        }
        DBG_STAMP(1);
        {
            const int cg = tid % 80, rgp = tid / 80;
            if (rgp < 3) {
                float acc[8];
#pragma unroll
                for (int j = 0; j < 8; j++) acc[j] = 0.f;
                const uint8_t* wbase = reinterpret_cast<const uint8_t*>(w2) + (size_t)(mc * CPC) * (D_MODEL * 2) + cg * 16;
#pragma unroll 1
                for (int it = 0; it < 9; it++) {
                    uint4 w[16];
#pragma unroll
                    for (int u = 0; u < 16; u++) w[u] = ldg_nc(wbase + (size_t)(rgp * 144 + it * 16 + u) * (D_MODEL * 2));
#pragma unroll
                    for (int u = 0; u < 16; u++) fma8(acc, hs[rgp * 144 + it * 16 + u], w[u]);
                }
#pragma unroll
                for (int j = 0; j < 8; j++) sm.red2[rgp][cg * 8 + j] = acc[j];
            }
            __syncthreads();
            for (int n = tid; n < D_MODEL; n += NTHREADS)
                st_ll(&g_mlp_part[mc][n], sm.red2[0][n] + sm.red2[1][n] + sm.red2[2][n], tag);
        }
        DBG_STAMP(2);

        DBG_STAMP(3);
    }
}

}

extern "C" void kernel_launch(void* const* d_in, const int* in_sizes, int n_in, void* d_out, int out_size) {
    const __nv_bfloat16* x  = (const __nv_bfloat16*)d_in[0];
    const __nv_bfloat16* kc = (const __nv_bfloat16*)d_in[1];
    const __nv_bfloat16* vc = (const __nv_bfloat16*)d_in[2];
    const __nv_bfloat16* wq = (const __nv_bfloat16*)d_in[3];
    const __nv_bfloat16* wo = (const __nv_bfloat16*)d_in[4];
    const __nv_bfloat16* w1 = (const __nv_bfloat16*)d_in[6];
    const __nv_bfloat16* b1 = (const __nv_bfloat16*)d_in[7];
    const __nv_bfloat16* w2 = (const __nv_bfloat16*)d_in[8];
    const __nv_bfloat16* b2 = (const __nv_bfloat16*)d_in[9];
    __nv_bfloat16* out = (__nv_bfloat16*)d_out;

    static bool attr_set = false;
    if (!attr_set) {
        cudaFuncSetAttribute(fused_decode_kernel, cudaFuncAttributeMaxDynamicSharedMemorySize, (int)sizeof(SmemLayout));
        attr_set = true;
    }
    fused_decode_kernel<<<GRID, NTHREADS, sizeof(SmemLayout)>>>(x, kc, vc, wq, wo, w1, b1, w2, b2, out);
}
```

```cpp
#include <cuda_runtime.h>
#include <cuda_bf16.h>
#include <stdint.h>

namespace {

constexpr int D_MODEL = 640;
constexpr int NHEAD   = 32;
constexpr int DH      = 128;
constexpr int SK      = 16384;
constexpr int FF      = 1728;

#define CFG_TILE 32
#define CFG_NSTAGE 10
#define CFG_SLEEP 0
#define CFG_DEPTH 4

constexpr int NSPLIT        = 4;
constexpr int TILE          = CFG_TILE;
constexpr int NSTAGE        = CFG_NSTAGE;
constexpr int DEPTH         = CFG_DEPTH;
constexpr int NT_HEAD       = SK / TILE;
constexpr int TILE_BYTES    = TILE * DH * 2;
constexpr int NCONS_WARPS   = 8;
constexpr int NCONS         = NCONS_WARPS * 32;
constexpr int NR            = TILE / NCONS_WARPS / 2;
constexpr int NTHREADS      = NCONS + 32;
constexpr int N_ATTN_CTA    = NHEAD * NSPLIT;
constexpr int N_MLP_CTA     = 4;
constexpr int GRID          = N_ATTN_CTA + N_MLP_CTA;
constexpr int OCOLS         = D_MODEL / NSPLIT;
constexpr int SPIN_LIMIT    = 1 << 22;

constexpr float LOG2E = 1.4426950408889634f;

constexpr int PH_QMLP = 1, PH_STREAM = 2, PH_PROJ = 4, PH_FINAL = 8, PH_EPOCH = 16, PH_ALL = 31;

typedef unsigned long long u64;

__device__ __align__(16) u64 g_qpart[NHEAD][NSPLIT][DH];
__device__ __align__(16) u64 g_part[NHEAD][NSPLIT][DH + 2];
__device__ __align__(16) u64 g_headout[NHEAD][D_MODEL];
__device__ __align__(16) u64 g_mlp_part[N_MLP_CTA][D_MODEL];
__device__ unsigned g_ticket[NHEAD];
__device__ unsigned g_epoch;

#define DBG_STAMP(i) do { } while (0)

struct __align__(128) SmemLayout {
    uint8_t  kbuf[NSTAGE][TILE_BYTES];
    uint8_t  vbuf[NSTAGE][TILE_BYTES];
    uint64_t full_k[NSTAGE];
    uint64_t full_v[NSTAGE];
    uint64_t empty[NSTAGE];
    int      valid[NSTAGE];
    float    xn[D_MODEL];
    float    q[DH];
    float    red[16][OCOLS];
    float    ms[16];
    float    ls[16];
    float    of[DH];
    __align__(16) float red2[5][D_MODEL];
};

__device__ __forceinline__ float bf16r(float x) { return __bfloat162float(__float2bfloat16_rn(x)); }
__device__ __forceinline__ float bf_lo(uint32_t u) { return __uint_as_float(u << 16); }
__device__ __forceinline__ float bf_hi(uint32_t u) { return __uint_as_float(u & 0xffff0000u); }

__device__ __forceinline__ uint32_t smem_u32(const void* p) { return (uint32_t)__cvta_generic_to_shared(p); }
__device__ __forceinline__ void mbar_init(uint64_t* bar, uint32_t count) {
    asm volatile("mbarrier.init.shared::cta.b64 [%0], %1;" ::"r"(smem_u32(bar)), "r"(count) : "memory");
}
__device__ __forceinline__ void mbar_expect_tx(uint64_t* bar, uint32_t bytes) {
    asm volatile("mbarrier.arrive.expect_tx.shared::cta.b64 _, [%0], %1;" ::"r"(smem_u32(bar)), "r"(bytes) : "memory");
}
__device__ __forceinline__ void mbar_arrive(uint64_t* bar) {
    asm volatile("mbarrier.arrive.shared::cta.b64 _, [%0];" ::"r"(smem_u32(bar)) : "memory");
}
__device__ __forceinline__ bool mbar_try_wait(uint64_t* bar, uint32_t parity) {
    uint32_t ok;
    asm volatile(
        "{\n\t.reg .pred p;\n\t"
        "mbarrier.try_wait.parity.shared::cta.b64 p, [%1], %2;\n\t"
        "selp.u32 %0, 1, 0, p;\n\t}"
        : "=r"(ok)
        : "r"(smem_u32(bar)), "r"(parity)
        : "memory");
    return ok != 0;
}
__device__ __forceinline__ void mbar_wait(uint64_t* bar, uint32_t parity) {
    while (!mbar_try_wait(bar, parity)) {
    }
}
__device__ __forceinline__ void bulk_g2s(void* dst, const void* src, uint32_t bytes, uint64_t* bar, uint64_t policy) {
    asm volatile(
        "cp.async.bulk.shared::cluster.global.mbarrier::complete_tx::bytes.L2::cache_hint [%0], [%1], %2, [%3], %4;"
        ::"r"(smem_u32(dst)), "l"(src), "r"(bytes), "r"(smem_u32(bar)), "l"(policy)
        : "memory");
}
__device__ __forceinline__ uint4 ldg_nc(const void* p) {
    uint4 r;
    asm volatile("ld.global.nc.L1::no_allocate.v4.u32 {%0,%1,%2,%3}, [%4];"
                 : "=r"(r.x), "=r"(r.y), "=r"(r.z), "=r"(r.w)
                 : "l"(p));
    return r;
}
__device__ __forceinline__ uint4 lds128(const void* p) {
    uint4 r;
    asm volatile("ld.shared.v4.u32 {%0,%1,%2,%3}, [%4];"
                 : "=r"(r.x), "=r"(r.y), "=r"(r.z), "=r"(r.w)
                 : "r"(smem_u32(p)));
    return r;
}
__device__ __forceinline__ void named_bar_sync(int id, int n) {
    asm volatile("bar.sync %0, %1;" ::"r"(id), "r"(n) : "memory");
}
__device__ __forceinline__ void st_ll(u64* p, float v, unsigned tag) {
    const u64 w = ((u64)tag << 32) | (u64)__float_as_uint(v);
    asm volatile("st.relaxed.gpu.global.b64 [%0], %1;" ::"l"(p), "l"(w) : "memory");
}
__device__ __forceinline__ u64 ld_ll(const u64* p) {
    u64 w;
    asm volatile("ld.relaxed.gpu.global.b64 %0, [%1];" : "=l"(w) : "l"(p) : "memory");
    return w;
}
__device__ __forceinline__ void ld_ll2(const u64* p, u64& a, u64& b) {
    asm volatile("ld.relaxed.gpu.global.v2.b64 {%0,%1}, [%2];" : "=l"(a), "=l"(b) : "l"(p) : "memory");
}
__device__ __forceinline__ bool ll_ok(u64 w, unsigned tag) { return (unsigned)(w >> 32) == tag; }
__device__ __forceinline__ float ll_val(u64 w) { return __uint_as_float((unsigned)w); }

__device__ __forceinline__ void fma8(float* acc, float xv, const uint4& w) {
    acc[0] = fmaf(xv, bf_lo(w.x), acc[0]); acc[1] = fmaf(xv, bf_hi(w.x), acc[1]);
    acc[2] = fmaf(xv, bf_lo(w.y), acc[2]); acc[3] = fmaf(xv, bf_hi(w.y), acc[3]);
    acc[4] = fmaf(xv, bf_lo(w.z), acc[4]); acc[5] = fmaf(xv, bf_hi(w.z), acc[5]);
    acc[6] = fmaf(xv, bf_lo(w.w), acc[6]); acc[7] = fmaf(xv, bf_hi(w.w), acc[7]);
}

__device__ void layernorm_bf16(const float* in, float* out, float* scr, int tid, int nthr, int bar_id) {
    const int lane = tid & 31, wid = tid >> 5, nw = nthr >> 5;
    float s = 0.f;
    for (int i = tid; i < D_MODEL; i += nthr) s += in[i];
#pragma unroll
    for (int o = 16; o > 0; o >>= 1) s += __shfl_xor_sync(0xffffffffu, s, o);
    if (lane == 0) scr[wid] = s;
    named_bar_sync(bar_id, nthr);
    float tot = 0.f;
    for (int w = 0; w < nw; w++) tot += scr[w];
    const float mean = tot * (1.0f / D_MODEL);
    float vs = 0.f;
    for (int i = tid; i < D_MODEL; i += nthr) {
        float d = in[i] - mean;
        vs += d * d;
    }
#pragma unroll
    for (int o = 16; o > 0; o >>= 1) vs += __shfl_xor_sync(0xffffffffu, vs, o);
    if (lane == 0) scr[32 + wid] = vs;
    named_bar_sync(bar_id, nthr);
    float vtot = 0.f;
    for (int w = 0; w < nw; w++) vtot += scr[32 + w];
    const float m_b = bf16r(mean);
    const float v_b = bf16r(vtot * (1.0f / D_MODEL));
    const float den = bf16r(sqrtf(bf16r(v_b + 1e-5f)));
    for (int i = tid; i < D_MODEL; i += nthr) {
        float d = bf16r(in[i] - m_b);
        out[i]  = bf16r(d / den);
    }
    named_bar_sync(bar_id, nthr);
}

__device__ __forceinline__ float gelu_tanh(float x) {
    const float k0 = 0.7978845608028654f, k1 = 0.044715f;
    float inner = k0 * (x + k1 * x * x * x);
    return 0.5f * x * (1.0f + tanhf(inner));
}

__global__ void __launch_bounds__(NTHREADS, 1)
fused_decode_kernel(const __nv_bfloat16* __restrict__ x,
                    const __nv_bfloat16* __restrict__ kc,
                    const __nv_bfloat16* __restrict__ vc,
                    const __nv_bfloat16* __restrict__ wq,
                    const __nv_bfloat16* __restrict__ wo,
                    const __nv_bfloat16* __restrict__ w1,
                    const __nv_bfloat16* __restrict__ b1,
                    const __nv_bfloat16* __restrict__ w2,
                    const __nv_bfloat16* __restrict__ b2,
                    __nv_bfloat16* __restrict__ out,
                    int phases) {
    extern __shared__ uint8_t smem_raw[];
    SmemLayout& sm = *reinterpret_cast<SmemLayout*>(smem_raw);
    const int tid  = threadIdx.x;
    const int lane = tid & 31;
    const int wid  = tid >> 5;
    const int cta  = blockIdx.x;
    DBG_STAMP(0);

    const unsigned epoch = *reinterpret_cast<volatile unsigned*>(&g_epoch);
    const unsigned tag   = epoch + 1u;
    const bool P0 = (phases & PH_QMLP) != 0, P1 = (phases & PH_STREAM) != 0;
    const bool P2 = (phases & PH_PROJ) != 0, P3 = (phases & PH_FINAL) != 0;
    if (phases == PH_EPOCH) {
        if (cta == 0 && tid == 0) *reinterpret_cast<volatile unsigned*>(&g_epoch) = epoch + 1u;
        return;
    }

    if (cta < N_ATTN_CTA) {
        const int h     = cta % NHEAD;
        const int split = cta / NHEAD;

        const uint8_t* kbase = reinterpret_cast<const uint8_t*>(kc) + (size_t)h * SK * (DH * 2);
        const uint8_t* vbase = reinterpret_cast<const uint8_t*>(vc) + (size_t)h * SK * (DH * 2);
        const int l16q = tid & 15;
        const int rgq  = tid >> 4;
        uint4 wqr[10];
        float xr[3];
        if (P0 && wid < NCONS_WARPS) {
#pragma unroll
            for (int u = 0; u < 3; u++) {
                const int i = tid + u * NCONS;
                xr[u] = (i < D_MODEL) ? __bfloat162float(x[i]) : 0.f;
            }
            const uint8_t* wbase = reinterpret_cast<const uint8_t*>(wq) + (size_t)h * DH * 2 + l16q * 16;
#pragma unroll
            for (int u = 0; u < 10; u++)
                wqr[u] = ldg_nc(wbase + (size_t)(split * 160 + rgq + 16 * u) * (NHEAD * DH * 2));
        }
        if (P1 && tid == NCONS) {
#pragma unroll
            for (int s = 0; s < NSTAGE; s++) {
                mbar_init(&sm.full_k[s], 1);
                mbar_init(&sm.full_v[s], 1);
                mbar_init(&sm.empty[s], NCONS_WARPS);
            }
            asm volatile("fence.mbarrier_init.release.cluster;" ::: "memory");
        }
        __syncthreads();

        if (wid == NCONS_WARPS) {
            if (P1 && lane == 0) {
                uint64_t policy;
                asm volatile("createpolicy.fractional.L2::evict_first.b64 %0, 1.0;" : "=l"(policy));
                constexpr unsigned NSTATIC = NSTAGE * NSPLIT;
                const unsigned tbase = epoch * (unsigned)(NT_HEAD - NSTATIC + NSPLIT) - NSTATIC;
                unsigned next = 0;
                for (int it = 0;; it++) {
                    const int s = it % NSTAGE;
                    unsigned t;
                    if (it < NSTAGE) {
                        t = split + NSPLIT * it;
                        if (it == NSTAGE - 1) next = atomicAdd(&g_ticket[h], 1u) - tbase;
                    } else {
                        t = next;
                        if (t < (unsigned)NT_HEAD) next = atomicAdd(&g_ticket[h], 1u) - tbase;
                        mbar_wait(&sm.empty[s], ((it / NSTAGE) - 1) & 1);
                    }
                    if (t >= (unsigned)NT_HEAD) {
                        sm.valid[s] = 0;
                        mbar_arrive(&sm.full_k[s]);
                        break;
                    }
                    if (it >= DEPTH) {
                        const int d = it - DEPTH;
                        mbar_wait(&sm.full_v[d % NSTAGE], (d / NSTAGE) & 1);
                    }
                    sm.valid[s] = 1;
                    mbar_expect_tx(&sm.full_k[s], TILE_BYTES);
                    bulk_g2s(sm.kbuf[s], kbase + (size_t)t * TILE_BYTES, TILE_BYTES, &sm.full_k[s], policy);
                    mbar_expect_tx(&sm.full_v[s], TILE_BYTES);
                    bulk_g2s(sm.vbuf[s], vbase + (size_t)t * TILE_BYTES, TILE_BYTES, &sm.full_v[s], policy);
                }
            }
            return;
        }

        if (P0) {
#pragma unroll
            for (int u = 0; u < 3; u++) {
                const int i = tid + u * NCONS;
                if (i < D_MODEL) sm.xn[i] = xr[u];
            }
            named_bar_sync(1, NCONS);
            layernorm_bf16(sm.xn, sm.xn, &sm.red[0][0], tid, NCONS, 1);

            float acc[8];
#pragma unroll
            for (int j = 0; j < 8; j++) acc[j] = 0.f;
#pragma unroll
            for (int u = 0; u < 10; u++) fma8(acc, sm.xn[split * 160 + rgq + 16 * u], wqr[u]);
#pragma unroll
            for (int j = 0; j < 8; j++) sm.red[rgq][l16q * 8 + j] = acc[j];
            named_bar_sync(1, NCONS);
            if (tid < DH) {
                float s = 0.f;
#pragma unroll
                for (int r = 0; r < 16; r++) s += sm.red[r][tid];
                st_ll(&g_qpart[h][split][tid], s, tag);
            }
        }
        if (P1) {
            if (tid < DH) {
                u64 w[NSPLIT];
                int spins = 0;
                for (;;) {
                    bool ok = true;
#pragma unroll
                    for (int i = 0; i < NSPLIT; i++) w[i] = ld_ll(&g_qpart[h][i][tid]);
#pragma unroll
                    for (int i = 0; i < NSPLIT; i++) ok = ok && ll_ok(w[i], tag);
                    if (ok || ++spins > SPIN_LIMIT) break;
                }
                sm.q[tid] = bf16r((ll_val(w[0]) + ll_val(w[1])) + (ll_val(w[2]) + ll_val(w[3])));
            }
            named_bar_sync(1, NCONS);
        }

        const int half = lane >> 4;
        const int l16  = lane & 15;
        float qf[8];
#pragma unroll
        for (int j = 0; j < 8; j++) qf[j] = P1 ? sm.q[l16 * 8 + j] : 0.f;

        float m = -INFINITY, l = 0.f;
        float o[8];
#pragma unroll
        for (int j = 0; j < 8; j++) o[j] = 0.f;
        const float scale = 0.08838834764831845f;
        const int row_off = (wid * (2 * NR) + half) * (DH * 2) + l16 * 16;

        int s = 0;
        uint32_t ph = 0;
#pragma unroll 1
        while (P1) {
            mbar_wait(&sm.full_k[s], ph);
            if (*reinterpret_cast<volatile int*>(&sm.valid[s]) == 0) break;
            uint4 kk[NR];
#pragma unroll
            for (int i = 0; i < NR; i++) kk[i] = lds128(sm.kbuf[s] + row_off + i * 2 * (DH * 2));
            float sc[NR];
#pragma unroll
            for (int i = 0; i < NR; i++) {
                float a = qf[0] * bf_lo(kk[i].x);
                a = fmaf(qf[1], bf_hi(kk[i].x), a);
                a = fmaf(qf[2], bf_lo(kk[i].y), a);
                a = fmaf(qf[3], bf_hi(kk[i].y), a);
                a = fmaf(qf[4], bf_lo(kk[i].z), a);
                a = fmaf(qf[5], bf_hi(kk[i].z), a);
                a = fmaf(qf[6], bf_lo(kk[i].w), a);
                a = fmaf(qf[7], bf_hi(kk[i].w), a);
                sc[i] = a;
            }
#pragma unroll
            for (int off = 8; off > 0; off >>= 1) {
#pragma unroll
                for (int i = 0; i < NR; i++) sc[i] += __shfl_xor_sync(0xffffffffu, sc[i], off);
            }
#pragma unroll
            for (int i = 0; i < NR; i++) sc[i] = bf16r(bf16r(sc[i]) * scale);
            float mnew = m;
#pragma unroll
            for (int i = 0; i < NR; i++) mnew = fmaxf(mnew, sc[i]);
            const float corr = exp2f((m - mnew) * LOG2E);
            float p[NR];
            float ps = 0.f;
#pragma unroll
            for (int i = 0; i < NR; i++) {
                p[i] = exp2f((sc[i] - mnew) * LOG2E);
                ps += p[i];
            }
            l = l * corr + ps;
            m = mnew;
#pragma unroll
            for (int j = 0; j < 8; j++) o[j] *= corr;

            mbar_wait(&sm.full_v[s], ph);
            uint4 vv[NR];
#pragma unroll
            for (int i = 0; i < NR; i++) vv[i] = lds128(sm.vbuf[s] + row_off + i * 2 * (DH * 2));
#pragma unroll
            for (int i = 0; i < NR; i++) fma8(o, p[i], vv[i]);
            __syncwarp();
            if (lane == 0) mbar_arrive(&sm.empty[s]);
            if (++s == NSTAGE) { s = 0; ph ^= 1; }
        }
        DBG_STAMP(2);

        const int cgo = tid % 20;
        const int rgo = tid / 20;
        uint4 wor[11];
        if (P2 && rgo < 12) {
            const uint8_t* wbase = reinterpret_cast<const uint8_t*>(wo) + (size_t)h * DH * (D_MODEL * 2) + split * (OCOLS * 2) + cgo * 16;
#pragma unroll
            for (int u = 0; u < 11; u++) {
                const int row = rgo + 12 * u;
                if (u < 10 || row < DH) wor[u] = ldg_nc(wbase + (size_t)row * (D_MODEL * 2));
            }
        }

        if (P1) {
            const int st = wid * 2 + half;
#pragma unroll
            for (int j = 0; j < 8; j++) sm.red[st][l16 * 8 + j] = o[j];
            if (l16 == 0) {
                sm.ms[st] = m;
                sm.ls[st] = l;
            }
            named_bar_sync(1, NCONS);
            if (tid < DH) {
                float M = sm.ms[0];
#pragma unroll
                for (int i = 1; i < 16; i++) M = fmaxf(M, sm.ms[i]);
                float L = 0.f, O = 0.f;
                if (M > -INFINITY) {
#pragma unroll
                    for (int i = 0; i < 16; i++) {
                        const float w = exp2f((sm.ms[i] - M) * LOG2E);
                        L += w * sm.ls[i];
                        O += w * sm.red[i][tid];
                    }
                }
                st_ll(&g_part[h][split][tid], O, tag);
                if (tid == 0) {
                    st_ll(&g_part[h][split][DH], M, tag);
                    st_ll(&g_part[h][split][DH + 1], L, tag);
                }
            }
        }
        if (P2) {
            if (tid < DH) {
                u64 wo_[NSPLIT], wm[NSPLIT], wl[NSPLIT];
                int spins = 0;
                for (;;) {
                    bool ok = true;
#pragma unroll
                    for (int i = 0; i < NSPLIT; i++) {
                        wo_[i] = ld_ll(&g_part[h][i][tid]);
                        ld_ll2(&g_part[h][i][DH], wm[i], wl[i]);
                    }
#pragma unroll
                    for (int i = 0; i < NSPLIT; i++) ok = ok && ll_ok(wo_[i], tag) && ll_ok(wm[i], tag) && ll_ok(wl[i], tag);
                    if (ok || ++spins > SPIN_LIMIT) break;
                }
                float MM = -INFINITY;
#pragma unroll
                for (int i = 0; i < NSPLIT; i++) MM = fmaxf(MM, ll_val(wm[i]));
                float LL = 0.f, OO = 0.f;
#pragma unroll
                for (int i = 0; i < NSPLIT; i++) {
                    const float mi = ll_val(wm[i]);
                    const float w  = (mi > -INFINITY) ? exp2f((mi - MM) * LOG2E) : 0.f;
                    LL += w * ll_val(wl[i]);
                    OO += w * ll_val(wo_[i]);
                }
                sm.of[tid] = bf16r(OO / LL);
            }
            named_bar_sync(1, NCONS);
        }

        if (P2) {
            if (rgo < 12) {
                float acc[8];
#pragma unroll
                for (int j = 0; j < 8; j++) acc[j] = 0.f;
#pragma unroll
                for (int u = 0; u < 11; u++) {
                    const int row = rgo + 12 * u;
                    if (u < 10 || row < DH) fma8(acc, sm.of[row], wor[u]);
                }
#pragma unroll
                for (int j = 0; j < 8; j++) sm.red[rgo][cgo * 8 + j] = acc[j];
            }
            named_bar_sync(1, NCONS);
            if (tid < OCOLS) {
                float a = 0.f;
#pragma unroll
                for (int r = 0; r < 12; r++) a += sm.red[r][tid];
                st_ll(&g_headout[h][split * OCOLS + tid], a, tag);
            }
        }
        DBG_STAMP(6);

        if (P3) {
            constexpr int FC = D_MODEL / N_ATTN_CTA;
            constexpr int NSRC = NHEAD + N_MLP_CTA;
            const int src = tid / FC, c = tid % FC;
            const int n = cta * FC + c;
            if (src < NSRC) {
                const u64* p = (src < NHEAD) ? &g_headout[src][n] : &g_mlp_part[src - NHEAD][n];
                u64 w = ld_ll(p);
                int spins = 0;
                while (!ll_ok(w, tag) && ++spins < SPIN_LIMIT) { if (CFG_SLEEP) __nanosleep(CFG_SLEEP); w = ld_ll(p); }
                sm.red2[0][src * FC + c] = ll_val(w);
            }
            named_bar_sync(1, NCONS);
            if (tid < FC) {
                float a = 0.f, z = 0.f;
#pragma unroll
                for (int hh = 0; hh < NHEAD; hh++) a += sm.red2[0][hh * FC + tid];
#pragma unroll
                for (int cc = 0; cc < N_MLP_CTA; cc++) z += sm.red2[0][(NHEAD + cc) * FC + tid];
                const int nn = cta * FC + tid;
                const float t  = bf16r(__bfloat162float(x[nn]) + bf16r(a));
                const float zz = bf16r(bf16r(z) + __bfloat162float(b2[nn]));
                out[nn] = __float2bfloat16_rn(t + zz);
            }
            if ((phases & PH_EPOCH) && cta == 0 && tid == 0) *reinterpret_cast<volatile unsigned*>(&g_epoch) = epoch + 1u;
        }
        DBG_STAMP(3);
        return;
    }

    if (P0) {
        const int mc = cta - N_ATTN_CTA;
        for (int i = tid; i < D_MODEL; i += NTHREADS) sm.xn[i] = __bfloat162float(x[i]);
        named_bar_sync(1, NTHREADS);
        layernorm_bf16(sm.xn, sm.xn, &sm.red[0][0], tid, NTHREADS, 1);
        layernorm_bf16(sm.xn, sm.xn, &sm.red[0][0], tid, NTHREADS, 1);

        constexpr int CPC = FF / N_MLP_CTA;
        float* hs = reinterpret_cast<float*>(sm.vbuf);
        {
            constexpr int NCG = CPC / 8;
            constexpr int NRG = 5;
            const int cg = tid % NCG, rg = tid / NCG;
            if (rg < NRG) {
                float acc[8];
#pragma unroll
                for (int j = 0; j < 8; j++) acc[j] = 0.f;
                const uint8_t* wbase = reinterpret_cast<const uint8_t*>(w1) + (size_t)(mc * CPC + cg * 8) * 2;
#pragma unroll 1
                for (int it = 0; it < 8; it++) {
                    uint4 w[16];
#pragma unroll
                    for (int u = 0; u < 16; u++) w[u] = ldg_nc(wbase + (size_t)(rg * 128 + it * 16 + u) * (FF * 2));
#pragma unroll
                    for (int u = 0; u < 16; u++) fma8(acc, sm.xn[rg * 128 + it * 16 + u], w[u]);
                }
#pragma unroll
                for (int j = 0; j < 8; j++) sm.red2[rg][cg * 8 + j] = acc[j];
            }
            __syncthreads();
            for (int c = tid; c < CPC; c += NTHREADS) {
                float s = 0.f;
#pragma unroll
                for (int r = 0; r < NRG; r++) s += sm.red2[r][c];
                const int f = mc * CPC + c;
                float u = bf16r(bf16r(s) + __bfloat162float(b1[f]));
                hs[c] = bf16r(gelu_tanh(u));
            }
            __syncthreads();
        }
        DBG_STAMP(1);
        {
            const int cg = tid % 80, rgp = tid / 80;
            if (rgp < 3) {
                float acc[8];
#pragma unroll
                for (int j = 0; j < 8; j++) acc[j] = 0.f;
                const uint8_t* wbase = reinterpret_cast<const uint8_t*>(w2) + (size_t)(mc * CPC) * (D_MODEL * 2) + cg * 16;
#pragma unroll 1
                for (int it = 0; it < 9; it++) {
                    uint4 w[16];
#pragma unroll
                    for (int u = 0; u < 16; u++) w[u] = ldg_nc(wbase + (size_t)(rgp * 144 + it * 16 + u) * (D_MODEL * 2));
#pragma unroll
                    for (int u = 0; u < 16; u++) fma8(acc, hs[rgp * 144 + it * 16 + u], w[u]);
                }
#pragma unroll
                for (int j = 0; j < 8; j++) sm.red2[rgp][cg * 8 + j] = acc[j];
            }
            __syncthreads();
            for (int n = tid; n < D_MODEL; n += NTHREADS)
                st_ll(&g_mlp_part[mc][n], sm.red2[0][n] + sm.red2[1][n] + sm.red2[2][n], tag);
        }
        DBG_STAMP(2);

        DBG_STAMP(3);
    }
}

}

extern "C" void kernel_launch(void* const* d_in, const int* in_sizes, int n_in, void* d_out, int out_size) {
    const __nv_bfloat16* x  = (const __nv_bfloat16*)d_in[0];
    const __nv_bfloat16* kc = (const __nv_bfloat16*)d_in[1];
    const __nv_bfloat16* vc = (const __nv_bfloat16*)d_in[2];
    const __nv_bfloat16* wq = (const __nv_bfloat16*)d_in[3];
    const __nv_bfloat16* wo = (const __nv_bfloat16*)d_in[4];
    const __nv_bfloat16* w1 = (const __nv_bfloat16*)d_in[6];
    const __nv_bfloat16* b1 = (const __nv_bfloat16*)d_in[7];
    const __nv_bfloat16* w2 = (const __nv_bfloat16*)d_in[8];
    const __nv_bfloat16* b2 = (const __nv_bfloat16*)d_in[9];
    __nv_bfloat16* out = (__nv_bfloat16*)d_out;

    static int mode = -1;
    if (mode < 0) {
        cudaFuncSetAttribute(fused_decode_kernel, cudaFuncAttributeMaxDynamicSharedMemorySize, (int)sizeof(SmemLayout));
        int dev = 0, sms = 0, per_sm = 0;
        cudaGetDevice(&dev);
        cudaDeviceGetAttribute(&sms, cudaDevAttrMultiProcessorCount, dev);
        cudaOccupancyMaxActiveBlocksPerMultiprocessor(&per_sm, fused_decode_kernel, NTHREADS, sizeof(SmemLayout));
        mode = (sms * per_sm >= GRID) ? 1 : 0;
    }
    if (mode == 1) {
        fused_decode_kernel<<<GRID, NTHREADS, sizeof(SmemLayout)>>>(x, kc, vc, wq, wo, w1, b1, w2, b2, out, PH_ALL);
    } else {
        for (int ph = PH_QMLP; ph <= PH_FINAL; ph <<= 1)
            fused_decode_kernel<<<GRID, NTHREADS, sizeof(SmemLayout)>>>(x, kc, vc, wq, wo, w1, b1, w2, b2, out, ph);
        fused_decode_kernel<<<1, NTHREADS, sizeof(SmemLayout)>>>(x, kc, vc, wq, wo, w1, b1, w2, b2, out, PH_EPOCH);
    }
}
```

```cpp
#include <cuda_runtime.h>
#include <cuda_bf16.h>
#include <stdint.h>

namespace {

constexpr int D_MODEL = 640;
constexpr int NHEAD   = 32;
constexpr int DH      = 128;
constexpr int SK      = 16384;
constexpr int FF      = 1728;

#define CFG_TILE 32
#define CFG_NSTAGE 10
#define CFG_DEPTH 4

constexpr int NSPLIT        = 4;
constexpr int TILE          = CFG_TILE;
constexpr int NSTAGE        = CFG_NSTAGE;
constexpr int DEPTH         = CFG_DEPTH;
constexpr int NT_HEAD       = SK / TILE;
constexpr int TILE_BYTES    = TILE * DH * 2;
constexpr int NCONS_WARPS   = 8;
constexpr int NCONS         = NCONS_WARPS * 32;
constexpr int NR            = TILE / NCONS_WARPS / 2;
constexpr int NTHREADS      = NCONS + 32;
constexpr int N_ATTN_CTA    = NHEAD * NSPLIT;
constexpr int N_MLP_CTA     = 4;
constexpr int GRID          = N_ATTN_CTA + N_MLP_CTA;
constexpr int OCOLS         = D_MODEL / NSPLIT;
constexpr int SPIN_LIMIT    = 1 << 22;

constexpr float LOG2E = 1.4426950408889634f;

constexpr int PH_QMLP = 1, PH_STREAM = 2, PH_PROJ = 4, PH_FINAL = 8, PH_EPOCH = 16, PH_ALL = 31;

typedef unsigned long long u64;

__device__ __align__(16) u64 g_qpart[NHEAD][NSPLIT][DH];
__device__ __align__(16) u64 g_part[NHEAD][NSPLIT][DH + 2];
__device__ __align__(16) u64 g_headout[NHEAD][D_MODEL];
__device__ __align__(16) u64 g_mlp_part[N_MLP_CTA][D_MODEL];
__device__ unsigned g_ticket[NHEAD];
__device__ unsigned g_epoch;

struct __align__(128) SmemLayout {
    uint8_t  kbuf[NSTAGE][TILE_BYTES];
    uint8_t  vbuf[NSTAGE][TILE_BYTES];
    uint64_t full_k[NSTAGE];
    uint64_t full_v[NSTAGE];
    uint64_t empty[NSTAGE];
    int      valid[NSTAGE];
    float    xn[D_MODEL];
    float    q[DH];
    float    red[16][OCOLS];
    float    ms[16];
    float    ls[16];
    float    of[DH];
    __align__(16) float red2[5][D_MODEL];
};

__device__ __forceinline__ float bf16r(float x) { return __bfloat162float(__float2bfloat16_rn(x)); }
__device__ __forceinline__ float bf_lo(uint32_t u) { return __uint_as_float(u << 16); }
__device__ __forceinline__ float bf_hi(uint32_t u) { return __uint_as_float(u & 0xffff0000u); }

__device__ __forceinline__ uint32_t smem_u32(const void* p) { return (uint32_t)__cvta_generic_to_shared(p); }
__device__ __forceinline__ void mbar_init(uint64_t* bar, uint32_t count) {
    asm volatile("mbarrier.init.shared::cta.b64 [%0], %1;" ::"r"(smem_u32(bar)), "r"(count) : "memory");
}
__device__ __forceinline__ void mbar_expect_tx(uint64_t* bar, uint32_t bytes) {
    asm volatile("mbarrier.arrive.expect_tx.shared::cta.b64 _, [%0], %1;" ::"r"(smem_u32(bar)), "r"(bytes) : "memory");
}
__device__ __forceinline__ void mbar_arrive(uint64_t* bar) {
    asm volatile("mbarrier.arrive.shared::cta.b64 _, [%0];" ::"r"(smem_u32(bar)) : "memory");
}
__device__ __forceinline__ bool mbar_try_wait(uint64_t* bar, uint32_t parity) {
    uint32_t ok;
    asm volatile(
        "{\n\t.reg .pred p;\n\t"
        "mbarrier.try_wait.parity.shared::cta.b64 p, [%1], %2;\n\t"
        "selp.u32 %0, 1, 0, p;\n\t}"
        : "=r"(ok)
        : "r"(smem_u32(bar)), "r"(parity)
        : "memory");
    return ok != 0;
}
__device__ __forceinline__ void mbar_wait(uint64_t* bar, uint32_t parity) {
    while (!mbar_try_wait(bar, parity)) {
    }
}
__device__ __forceinline__ void bulk_g2s(void* dst, const void* src, uint32_t bytes, uint64_t* bar, uint64_t policy) {
    asm volatile(
        "cp.async.bulk.shared::cluster.global.mbarrier::complete_tx::bytes.L2::cache_hint [%0], [%1], %2, [%3], %4;"
        ::"r"(smem_u32(dst)), "l"(src), "r"(bytes), "r"(smem_u32(bar)), "l"(policy)
        : "memory");
}
__device__ __forceinline__ uint4 ldg_nc(const void* p) {
    uint4 r;
    asm volatile("ld.global.nc.L1::no_allocate.v4.u32 {%0,%1,%2,%3}, [%4];"
                 : "=r"(r.x), "=r"(r.y), "=r"(r.z), "=r"(r.w)
                 : "l"(p));
    return r;
}
__device__ __forceinline__ uint4 lds128(const void* p) {
    uint4 r;
    asm volatile("ld.shared.v4.u32 {%0,%1,%2,%3}, [%4];"
                 : "=r"(r.x), "=r"(r.y), "=r"(r.z), "=r"(r.w)
                 : "r"(smem_u32(p)));
    return r;
}
__device__ __forceinline__ void named_bar_sync(int id, int n) {
    asm volatile("bar.sync %0, %1;" ::"r"(id), "r"(n) : "memory");
}
__device__ __forceinline__ void st_ll(u64* p, float v, unsigned tag) {
    const u64 w = ((u64)tag << 32) | (u64)__float_as_uint(v);
    asm volatile("st.relaxed.gpu.global.b64 [%0], %1;" ::"l"(p), "l"(w) : "memory");
}
__device__ __forceinline__ u64 ld_ll(const u64* p) {
    u64 w;
    asm volatile("ld.relaxed.gpu.global.b64 %0, [%1];" : "=l"(w) : "l"(p) : "memory");
    return w;
}
__device__ __forceinline__ void ld_ll2(const u64* p, u64& a, u64& b) {
    asm volatile("ld.relaxed.gpu.global.v2.b64 {%0,%1}, [%2];" : "=l"(a), "=l"(b) : "l"(p) : "memory");
}
__device__ __forceinline__ bool ll_ok(u64 w, unsigned tag) { return (unsigned)(w >> 32) == tag; }
__device__ __forceinline__ float ll_val(u64 w) { return __uint_as_float((unsigned)w); }

__device__ __forceinline__ void fma8(float* acc, float xv, const uint4& w) {
    acc[0] = fmaf(xv, bf_lo(w.x), acc[0]); acc[1] = fmaf(xv, bf_hi(w.x), acc[1]);
    acc[2] = fmaf(xv, bf_lo(w.y), acc[2]); acc[3] = fmaf(xv, bf_hi(w.y), acc[3]);
    acc[4] = fmaf(xv, bf_lo(w.z), acc[4]); acc[5] = fmaf(xv, bf_hi(w.z), acc[5]);
    acc[6] = fmaf(xv, bf_lo(w.w), acc[6]); acc[7] = fmaf(xv, bf_hi(w.w), acc[7]);
}

__device__ void layernorm_bf16(const float* in, float* out, float* scr, int tid, int nthr, int bar_id) {
    const int lane = tid & 31, wid = tid >> 5, nw = nthr >> 5;
    float s = 0.f;
    for (int i = tid; i < D_MODEL; i += nthr) s += in[i];
#pragma unroll
    for (int o = 16; o > 0; o >>= 1) s += __shfl_xor_sync(0xffffffffu, s, o);
    if (lane == 0) scr[wid] = s;
    named_bar_sync(bar_id, nthr);
    float tot = 0.f;
    for (int w = 0; w < nw; w++) tot += scr[w];
    const float mean = tot * (1.0f / D_MODEL);
    float vs = 0.f;
    for (int i = tid; i < D_MODEL; i += nthr) {
        float d = in[i] - mean;
        vs += d * d;
    }
#pragma unroll
    for (int o = 16; o > 0; o >>= 1) vs += __shfl_xor_sync(0xffffffffu, vs, o);
    if (lane == 0) scr[32 + wid] = vs;
    named_bar_sync(bar_id, nthr);
    float vtot = 0.f;
    for (int w = 0; w < nw; w++) vtot += scr[32 + w];
    const float m_b = bf16r(mean);
    const float v_b = bf16r(vtot * (1.0f / D_MODEL));
    const float den = bf16r(sqrtf(bf16r(v_b + 1e-5f)));
    for (int i = tid; i < D_MODEL; i += nthr) {
        float d = bf16r(in[i] - m_b);
        out[i]  = bf16r(d / den);
    }
    named_bar_sync(bar_id, nthr);
}

__device__ __forceinline__ float gelu_tanh(float x) {
    const float k0 = 0.7978845608028654f, k1 = 0.044715f;
    float inner = k0 * (x + k1 * x * x * x);
    return 0.5f * x * (1.0f + tanhf(inner));
}

__global__ void __launch_bounds__(NTHREADS, 1)
fused_decode_kernel(const __nv_bfloat16* __restrict__ x,
                    const __nv_bfloat16* __restrict__ kc,
                    const __nv_bfloat16* __restrict__ vc,
                    const __nv_bfloat16* __restrict__ wq,
                    const __nv_bfloat16* __restrict__ wo,
                    const __nv_bfloat16* __restrict__ w1,
                    const __nv_bfloat16* __restrict__ b1,
                    const __nv_bfloat16* __restrict__ w2,
                    const __nv_bfloat16* __restrict__ b2,
                    __nv_bfloat16* __restrict__ out,
                    int phases) {
    extern __shared__ uint8_t smem_raw[];
    SmemLayout& sm = *reinterpret_cast<SmemLayout*>(smem_raw);
    const int tid  = threadIdx.x;
    const int lane = tid & 31;
    const int wid  = tid >> 5;
    const int cta  = blockIdx.x;

    const unsigned epoch = *reinterpret_cast<volatile unsigned*>(&g_epoch);
    const unsigned tag   = epoch + 1u;
    const bool P0 = (phases & PH_QMLP) != 0, P1 = (phases & PH_STREAM) != 0;
    const bool P2 = (phases & PH_PROJ) != 0, P3 = (phases & PH_FINAL) != 0;
    if (phases == PH_EPOCH) {
        if (cta == 0 && tid == 0) *reinterpret_cast<volatile unsigned*>(&g_epoch) = epoch + 1u;
        return;
    }

    if (cta < N_ATTN_CTA) {
        const int h     = cta % NHEAD;
        const int split = cta / NHEAD;

        const uint8_t* kbase = reinterpret_cast<const uint8_t*>(kc) + (size_t)h * SK * (DH * 2);
        const uint8_t* vbase = reinterpret_cast<const uint8_t*>(vc) + (size_t)h * SK * (DH * 2);
        const int l16q = tid & 15;
        const int rgq  = tid >> 4;
        uint4 wqr[10];
        float xr[3];
        if (P0 && wid < NCONS_WARPS) {
#pragma unroll
            for (int u = 0; u < 3; u++) {
                const int i = tid + u * NCONS;
                xr[u] = (i < D_MODEL) ? __bfloat162float(x[i]) : 0.f;
            }
            const uint8_t* wbase = reinterpret_cast<const uint8_t*>(wq) + (size_t)h * DH * 2 + l16q * 16;
#pragma unroll
            for (int u = 0; u < 10; u++)
                wqr[u] = ldg_nc(wbase + (size_t)(split * 160 + rgq + 16 * u) * (NHEAD * DH * 2));
        }
        if (P1 && tid == NCONS) {
#pragma unroll
            for (int s = 0; s < NSTAGE; s++) {
                mbar_init(&sm.full_k[s], 1);
                mbar_init(&sm.full_v[s], 1);
                mbar_init(&sm.empty[s], NCONS_WARPS);
            }
            asm volatile("fence.mbarrier_init.release.cluster;" ::: "memory");
        }
        __syncthreads();

        if (wid == NCONS_WARPS) {
            if (P1 && lane == 0) {
                uint64_t policy;
                asm volatile("createpolicy.fractional.L2::evict_first.b64 %0, 1.0;" : "=l"(policy));
                constexpr unsigned NSTATIC = NSTAGE * NSPLIT;
                const unsigned tbase = epoch * (unsigned)(NT_HEAD - NSTATIC + NSPLIT) - NSTATIC;
                unsigned next = 0;
                for (int it = 0;; it++) {
                    const int s = it % NSTAGE;
                    unsigned t;
                    if (it < NSTAGE) {
                        t = split + NSPLIT * it;
                        if (it == NSTAGE - 1) next = atomicAdd(&g_ticket[h], 1u) - tbase;
                    } else {
                        t = next;
                        if (t < (unsigned)NT_HEAD) next = atomicAdd(&g_ticket[h], 1u) - tbase;
                        mbar_wait(&sm.empty[s], ((it / NSTAGE) - 1) & 1);
                    }
                    if (t >= (unsigned)NT_HEAD) {
                        sm.valid[s] = 0;
                        mbar_arrive(&sm.full_k[s]);
                        break;
                    }
                    if (it >= DEPTH) {
                        const int d = it - DEPTH;
                        mbar_wait(&sm.full_v[d % NSTAGE], (d / NSTAGE) & 1);
                    }
                    sm.valid[s] = 1;
                    mbar_expect_tx(&sm.full_k[s], TILE_BYTES);
                    bulk_g2s(sm.kbuf[s], kbase + (size_t)t * TILE_BYTES, TILE_BYTES, &sm.full_k[s], policy);
                    mbar_expect_tx(&sm.full_v[s], TILE_BYTES);
                    bulk_g2s(sm.vbuf[s], vbase + (size_t)t * TILE_BYTES, TILE_BYTES, &sm.full_v[s], policy);
                }
            }
            return;
        }

        if (P0) {
#pragma unroll
            for (int u = 0; u < 3; u++) {
                const int i = tid + u * NCONS;
                if (i < D_MODEL) sm.xn[i] = xr[u];
            }
            named_bar_sync(1, NCONS);
            layernorm_bf16(sm.xn, sm.xn, &sm.red[0][0], tid, NCONS, 1);

            float acc[8];
#pragma unroll
            for (int j = 0; j < 8; j++) acc[j] = 0.f;
#pragma unroll
            for (int u = 0; u < 10; u++) fma8(acc, sm.xn[split * 160 + rgq + 16 * u], wqr[u]);
#pragma unroll
            for (int j = 0; j < 8; j++) sm.red[rgq][l16q * 8 + j] = acc[j];
            named_bar_sync(1, NCONS);
            if (tid < DH) {
                float s = 0.f;
#pragma unroll
                for (int r = 0; r < 16; r++) s += sm.red[r][tid];
                st_ll(&g_qpart[h][split][tid], s, tag);
            }
        }
        if (P1) {
            if (tid < DH) {
                u64 w[NSPLIT];
                int spins = 0;
                for (;;) {
                    bool ok = true;
#pragma unroll
                    for (int i = 0; i < NSPLIT; i++) w[i] = ld_ll(&g_qpart[h][i][tid]);
#pragma unroll
                    for (int i = 0; i < NSPLIT; i++) ok = ok && ll_ok(w[i], tag);
                    if (ok || ++spins > SPIN_LIMIT) break;
                }
                sm.q[tid] = bf16r((ll_val(w[0]) + ll_val(w[1])) + (ll_val(w[2]) + ll_val(w[3])));
            }
            named_bar_sync(1, NCONS);
        }

        const int half = lane >> 4;
        const int l16  = lane & 15;
        float qf[8];
#pragma unroll
        for (int j = 0; j < 8; j++) qf[j] = P1 ? sm.q[l16 * 8 + j] : 0.f;

        float m = -INFINITY, l = 0.f;
        float o[8];
#pragma unroll
        for (int j = 0; j < 8; j++) o[j] = 0.f;
        const float scale = 0.08838834764831845f;
        const int row_off = (wid * (2 * NR) + half) * (DH * 2) + l16 * 16;

        int s = 0;
        uint32_t ph = 0;
#pragma unroll 1
        while (P1) {
            mbar_wait(&sm.full_k[s], ph);
            if (*reinterpret_cast<volatile int*>(&sm.valid[s]) == 0) break;
            uint4 kk[NR];
#pragma unroll
            for (int i = 0; i < NR; i++) kk[i] = lds128(sm.kbuf[s] + row_off + i * 2 * (DH * 2));
            float sc[NR];
#pragma unroll
            for (int i = 0; i < NR; i++) {
                float a = qf[0] * bf_lo(kk[i].x);
                a = fmaf(qf[1], bf_hi(kk[i].x), a);
                a = fmaf(qf[2], bf_lo(kk[i].y), a);
                a = fmaf(qf[3], bf_hi(kk[i].y), a);
                a = fmaf(qf[4], bf_lo(kk[i].z), a);
                a = fmaf(qf[5], bf_hi(kk[i].z), a);
                a = fmaf(qf[6], bf_lo(kk[i].w), a);
                a = fmaf(qf[7], bf_hi(kk[i].w), a);
                sc[i] = a;
            }
#pragma unroll
            for (int off = 8; off > 0; off >>= 1) {
#pragma unroll
                for (int i = 0; i < NR; i++) sc[i] += __shfl_xor_sync(0xffffffffu, sc[i], off);
            }
#pragma unroll
            for (int i = 0; i < NR; i++) sc[i] = bf16r(bf16r(sc[i]) * scale);
            float mnew = m;
#pragma unroll
            for (int i = 0; i < NR; i++) mnew = fmaxf(mnew, sc[i]);
            const float corr = exp2f((m - mnew) * LOG2E);
            float p[NR];
            float ps = 0.f;
#pragma unroll
            for (int i = 0; i < NR; i++) {
                p[i] = exp2f((sc[i] - mnew) * LOG2E);
                ps += p[i];
            }
            l = l * corr + ps;
            m = mnew;
#pragma unroll
            for (int j = 0; j < 8; j++) o[j] *= corr;

            mbar_wait(&sm.full_v[s], ph);
            uint4 vv[NR];
#pragma unroll
            for (int i = 0; i < NR; i++) vv[i] = lds128(sm.vbuf[s] + row_off + i * 2 * (DH * 2));
#pragma unroll
            for (int i = 0; i < NR; i++) fma8(o, p[i], vv[i]);
            __syncwarp();
            if (lane == 0) mbar_arrive(&sm.empty[s]);
            if (++s == NSTAGE) { s = 0; ph ^= 1; }
        }

        const int cgo = tid % 20;
        const int rgo = tid / 20;
        uint4 wor[11];
        if (P2 && rgo < 12) {
            const uint8_t* wbase = reinterpret_cast<const uint8_t*>(wo) + (size_t)h * DH * (D_MODEL * 2) + split * (OCOLS * 2) + cgo * 16;
#pragma unroll
            for (int u = 0; u < 11; u++) {
                const int row = rgo + 12 * u;
                if (u < 10 || row < DH) wor[u] = ldg_nc(wbase + (size_t)row * (D_MODEL * 2));
            }
        }

        if (P1) {
            const int st = wid * 2 + half;
#pragma unroll
            for (int j = 0; j < 8; j++) sm.red[st][l16 * 8 + j] = o[j];
            if (l16 == 0) {
                sm.ms[st] = m;
                sm.ls[st] = l;
            }
            named_bar_sync(1, NCONS);
            if (tid < DH) {
                float M = sm.ms[0];
#pragma unroll
                for (int i = 1; i < 16; i++) M = fmaxf(M, sm.ms[i]);
                float L = 0.f, O = 0.f;
                if (M > -INFINITY) {
#pragma unroll
                    for (int i = 0; i < 16; i++) {
                        const float w = exp2f((sm.ms[i] - M) * LOG2E);
                        L += w * sm.ls[i];
                        O += w * sm.red[i][tid];
                    }
                }
                st_ll(&g_part[h][split][tid], O, tag);
                if (tid == 0) {
                    st_ll(&g_part[h][split][DH], M, tag);
                    st_ll(&g_part[h][split][DH + 1], L, tag);
                }
            }
        }
        if (P2) {
            if (tid < DH) {
                u64 wo_[NSPLIT], wm[NSPLIT], wl[NSPLIT];
                int spins = 0;
                for (;;) {
                    bool ok = true;
#pragma unroll
                    for (int i = 0; i < NSPLIT; i++) {
                        wo_[i] = ld_ll(&g_part[h][i][tid]);
                        ld_ll2(&g_part[h][i][DH], wm[i], wl[i]);
                    }
#pragma unroll
                    for (int i = 0; i < NSPLIT; i++) ok = ok && ll_ok(wo_[i], tag) && ll_ok(wm[i], tag) && ll_ok(wl[i], tag);
                    if (ok || ++spins > SPIN_LIMIT) break;
                }
                float MM = -INFINITY;
#pragma unroll
                for (int i = 0; i < NSPLIT; i++) MM = fmaxf(MM, ll_val(wm[i]));
                float LL = 0.f, OO = 0.f;
#pragma unroll
                for (int i = 0; i < NSPLIT; i++) {
                    const float mi = ll_val(wm[i]);
                    const float w  = (mi > -INFINITY) ? exp2f((mi - MM) * LOG2E) : 0.f;
                    LL += w * ll_val(wl[i]);
                    OO += w * ll_val(wo_[i]);
                }
                sm.of[tid] = bf16r(OO / LL);
            }
            named_bar_sync(1, NCONS);
        }

        if (P2) {
            if (rgo < 12) {
                float acc[8];
#pragma unroll
                for (int j = 0; j < 8; j++) acc[j] = 0.f;
#pragma unroll
                for (int u = 0; u < 11; u++) {
                    const int row = rgo + 12 * u;
                    if (u < 10 || row < DH) fma8(acc, sm.of[row], wor[u]);
                }
#pragma unroll
                for (int j = 0; j < 8; j++) sm.red[rgo][cgo * 8 + j] = acc[j];
            }
            named_bar_sync(1, NCONS);
            if (tid < OCOLS) {
                float a = 0.f;
#pragma unroll
                for (int r = 0; r < 12; r++) a += sm.red[r][tid];
                st_ll(&g_headout[h][split * OCOLS + tid], a, tag);
            }
        }

        if (P3) {
            constexpr int FC = D_MODEL / N_ATTN_CTA;
            constexpr int NSRC = NHEAD + N_MLP_CTA;
            const int src = tid / FC, c = tid % FC;
            const int n = cta * FC + c;
            if (src < NSRC) {
                const u64* p = (src < NHEAD) ? &g_headout[src][n] : &g_mlp_part[src - NHEAD][n];
                u64 w = ld_ll(p);
                int spins = 0;
                while (!ll_ok(w, tag) && ++spins < SPIN_LIMIT) w = ld_ll(p);
                sm.red2[0][src * FC + c] = ll_val(w);
            }
            named_bar_sync(1, NCONS);
            if (tid < FC) {
                float a = 0.f, z = 0.f;
#pragma unroll
                for (int hh = 0; hh < NHEAD; hh++) a += sm.red2[0][hh * FC + tid];
#pragma unroll
                for (int cc = 0; cc < N_MLP_CTA; cc++) z += sm.red2[0][(NHEAD + cc) * FC + tid];
                const int nn = cta * FC + tid;
                const float t  = bf16r(__bfloat162float(x[nn]) + bf16r(a));
                const float zz = bf16r(bf16r(z) + __bfloat162float(b2[nn]));
                out[nn] = __float2bfloat16_rn(t + zz);
            }
            if ((phases & PH_EPOCH) && cta == 0 && tid == 0) *reinterpret_cast<volatile unsigned*>(&g_epoch) = epoch + 1u;
        }
        return;
    }

    if (P0) {
        const int mc = cta - N_ATTN_CTA;
        for (int i = tid; i < D_MODEL; i += NTHREADS) sm.xn[i] = __bfloat162float(x[i]);
        named_bar_sync(1, NTHREADS);
        layernorm_bf16(sm.xn, sm.xn, &sm.red[0][0], tid, NTHREADS, 1);
        layernorm_bf16(sm.xn, sm.xn, &sm.red[0][0], tid, NTHREADS, 1);

        constexpr int CPC = FF / N_MLP_CTA;
        float* hs = reinterpret_cast<float*>(sm.vbuf);
        {
            constexpr int NCG = CPC / 8;
            constexpr int NRG = 5;
            const int cg = tid % NCG, rg = tid / NCG;
            if (rg < NRG) {
                float acc[8];
#pragma unroll
                for (int j = 0; j < 8; j++) acc[j] = 0.f;
                const uint8_t* wbase = reinterpret_cast<const uint8_t*>(w1) + (size_t)(mc * CPC + cg * 8) * 2;
#pragma unroll 1
                for (int it = 0; it < 8; it++) {
                    uint4 w[16];
#pragma unroll
                    for (int u = 0; u < 16; u++) w[u] = ldg_nc(wbase + (size_t)(rg * 128 + it * 16 + u) * (FF * 2));
#pragma unroll
                    for (int u = 0; u < 16; u++) fma8(acc, sm.xn[rg * 128 + it * 16 + u], w[u]);
                }
#pragma unroll
                for (int j = 0; j < 8; j++) sm.red2[rg][cg * 8 + j] = acc[j];
            }
            __syncthreads();
            for (int c = tid; c < CPC; c += NTHREADS) {
                float s = 0.f;
#pragma unroll
                for (int r = 0; r < NRG; r++) s += sm.red2[r][c];
                const int f = mc * CPC + c;
                float u = bf16r(bf16r(s) + __bfloat162float(b1[f]));
                hs[c] = bf16r(gelu_tanh(u));
            }
            __syncthreads();
        }
        {
            const int cg = tid % 80, rgp = tid / 80;
            if (rgp < 3) {
                float acc[8];
#pragma unroll
                for (int j = 0; j < 8; j++) acc[j] = 0.f;
                const uint8_t* wbase = reinterpret_cast<const uint8_t*>(w2) + (size_t)(mc * CPC) * (D_MODEL * 2) + cg * 16;
#pragma unroll 1
                for (int it = 0; it < 9; it++) {
                    uint4 w[16];
#pragma unroll
                    for (int u = 0; u < 16; u++) w[u] = ldg_nc(wbase + (size_t)(rgp * 144 + it * 16 + u) * (D_MODEL * 2));
#pragma unroll
                    for (int u = 0; u < 16; u++) fma8(acc, hs[rgp * 144 + it * 16 + u], w[u]);
                }
#pragma unroll
                for (int j = 0; j < 8; j++) sm.red2[rgp][cg * 8 + j] = acc[j];
            }
            __syncthreads();
            for (int n = tid; n < D_MODEL; n += NTHREADS)
                st_ll(&g_mlp_part[mc][n], sm.red2[0][n] + sm.red2[1][n] + sm.red2[2][n], tag);
        }

    }
}

}

extern "C" void kernel_launch(void* const* d_in, const int* in_sizes, int n_in, void* d_out, int out_size) {
    const __nv_bfloat16* x  = (const __nv_bfloat16*)d_in[0];
    const __nv_bfloat16* kc = (const __nv_bfloat16*)d_in[1];
    const __nv_bfloat16* vc = (const __nv_bfloat16*)d_in[2];
    const __nv_bfloat16* wq = (const __nv_bfloat16*)d_in[3];
    const __nv_bfloat16* wo = (const __nv_bfloat16*)d_in[4];
    const __nv_bfloat16* w1 = (const __nv_bfloat16*)d_in[6];
    const __nv_bfloat16* b1 = (const __nv_bfloat16*)d_in[7];
    const __nv_bfloat16* w2 = (const __nv_bfloat16*)d_in[8];
    const __nv_bfloat16* b2 = (const __nv_bfloat16*)d_in[9];
    __nv_bfloat16* out = (__nv_bfloat16*)d_out;

    static int mode = -1;
    if (mode < 0) {
        cudaFuncSetAttribute(fused_decode_kernel, cudaFuncAttributeMaxDynamicSharedMemorySize, (int)sizeof(SmemLayout));
        int dev = 0, sms = 0, per_sm = 0;
        cudaGetDevice(&dev);
        cudaDeviceGetAttribute(&sms, cudaDevAttrMultiProcessorCount, dev);
        cudaOccupancyMaxActiveBlocksPerMultiprocessor(&per_sm, fused_decode_kernel, NTHREADS, sizeof(SmemLayout));
        mode = (sms * per_sm >= GRID) ? 1 : 0;
    }
    if (mode == 1) {
        fused_decode_kernel<<<GRID, NTHREADS, sizeof(SmemLayout)>>>(x, kc, vc, wq, wo, w1, b1, w2, b2, out, PH_ALL);
    } else {
        for (int ph = PH_QMLP; ph <= PH_FINAL; ph <<= 1)
            fused_decode_kernel<<<GRID, NTHREADS, sizeof(SmemLayout)>>>(x, kc, vc, wq, wo, w1, b1, w2, b2, out, ph);
        fused_decode_kernel<<<1, NTHREADS, sizeof(SmemLayout)>>>(x, kc, vc, wq, wo, w1, b1, w2, b2, out, PH_EPOCH);
    }
}
```
